```python
import torch

def _softmax(x, axis=-1):
    return torch.softmax(x, dim=axis)
def _gelu(x):
    return torch.nn.functional.gelu(x, approximate="tanh")
def _silu(x):
    return torch.nn.functional.silu(x)
def _sigmoid(x):
    return torch.sigmoid(x)
def _layernorm(x, axis=-1, eps=1e-5):
    m = x.mean(dim=axis, keepdim=True)
    v = x.var(dim=axis, keepdim=True, unbiased=False)
    return (x - m) / torch.sqrt(v + eps)
def _scatter_add(tgt, idx, src, axis=0):
    return tgt.clone().index_add_(axis, idx, src)
def _segment_sum(src, seg, n):
    out = torch.zeros((n,) + src.shape[1:], dtype=src.dtype)
    return out.index_add_(0, seg, src)
def _pad(x, pw):
    flat = tuple(v for pair in reversed(pw) for v in pair)
    return torch.nn.functional.pad(x, flat)

kernel_name = 'recurrent_scan__ssm_conv_s4d__moe_arch_mod__prompt'

def setup_inputs():

    _w = (lambda a: (lambda t: t.to(torch.bfloat16) if t.is_floating_point() else t)(torch.as_tensor(a)))
    def _A_setup():
        Bsz, L, D, N = 1, 2048, 1024, 128
        return {
            "u": _w((lambda *s: torch.randn(*s, dtype=torch.bfloat16) * 0.05)(Bsz, L, D)),
            "log_A_real": _w((lambda *s: torch.randn(*s, dtype=torch.bfloat16) * 6.4)(D, N) * 0.5),
            "A_imag": _w((lambda *s: torch.randn(*s, dtype=torch.bfloat16) * 0.05)(D, N) * 3.14),
            "C_real": _w((lambda *s: torch.randn(*s, dtype=torch.bfloat16) * 0.05)(D, N) / N ** 0.5),
            "C_imag": _w((lambda *s: torch.randn(*s, dtype=torch.bfloat16) * 0.05)(D, N) / N ** 0.5),
            "log_dt": _w((lambda *s: torch.randn(*s, dtype=torch.bfloat16) * 0.05)(D) * 0.5 - 4.0),
            "D_skip": _w((lambda *s: torch.randn(*s, dtype=torch.bfloat16) * 0.05)(D)),
        }
    _A_in = _A_setup()

    def _B_setup():
        B, S, D, F, C = 1, 2048, 1024, 3584, 2
        return {
            "x": _w((lambda *s: torch.randn(*s, dtype=torch.bfloat16) * 0.05)(B, S, D)),
            "w_r": _w((lambda *s: torch.randn(*s, dtype=torch.bfloat16) * 0.05)(D)),
            "w_gate": _w((lambda *s: torch.randn(*s, dtype=torch.bfloat16) * 0.05)(D, F)),
            "w_up": _w((lambda *s: torch.randn(*s, dtype=torch.bfloat16) * 0.05)(D, F)),
            "w_down": _w((lambda *s: torch.randn(*s, dtype=torch.bfloat16) * 0.05)(F, D)),
        }
    _B_in = _B_setup()

    return {
        "A_u": _A_in["u"],
        "A_log_A_real": _A_in["log_A_real"],
        "A_A_imag": _A_in["A_imag"],
        "A_C_real": _A_in["C_real"],
        "A_C_imag": _A_in["C_imag"],
        "A_log_dt": _A_in["log_dt"],
        "A_D_skip": _A_in["D_skip"],
        "B_x": _B_in["x"],
        "B_w_r": _B_in["w_r"],
        "B_w_gate": _B_in["w_gate"],
        "B_w_up": _B_in["w_up"],
        "B_w_down": _B_in["w_down"],
    }

def reference(A_u, A_log_A_real, A_A_imag, A_C_real, A_C_imag, A_log_dt, A_D_skip, B_x, B_w_r, B_w_gate, B_w_up, B_w_down):
    def _A_ref(u, log_A_real, A_imag, C_real, C_imag, log_dt, D_skip):
        L = u.shape[1]
        dt = torch.exp(log_dt)
        A = -torch.exp(log_A_real) + 1j * A_imag
        C = (C_real + 1j * C_imag) * dt[:, None]
        pos = (lambda x, dt: x.to(dt))(torch.arange(L), log_dt.dtype)
        P = torch.exp((A * dt[:, None])[:, :, None] * pos[None, None, :])
        K = 2.0 * torch.einsum("dn,dnl->dl", C, P).real
        L2 = 2 * L
        u_t = (lambda x, *d: x.permute(*d))(u, 0, 2, 1)
        Kf = (lambda x, *a, **k: torch.fft.rfft(x.float(), *a, **k))(K, L2)
        Uf = (lambda x, *a, **k: torch.fft.rfft(x.float(), *a, **k))(u_t, L2)
        y = (lambda x, *a, **k: torch.fft.irfft(x, *a, **k).to(torch.bfloat16))(Uf * Kf[None, :, :], L2)[:, :, :L]
        y = (lambda x, *d: x.permute(*d))(y, 0, 2, 1)
        return y + u * D_skip[None, None, :]

    def _B_ref(x, w_r, w_gate, w_up, w_down):
        B, S, D = x.shape
        C = 2
        r = x @ w_r
        idx = torch.argsort(-r, axis=-1)[:, :C]
        idx_e = (lambda x, n, axis: torch.repeat_interleave(x, n, dim=axis))(idx.reshape(B, C, 1), D, axis=2)
        x_sel = (lambda x, i, axis: torch.take_along_dim(x, i, dim=axis))(x, idx_e, axis=1)
        g = _silu(x_sel @ w_gate)
        u = x_sel @ w_up
        y = (g * u) @ w_down
        r_sel = _sigmoid((lambda x, i, axis: torch.take_along_dim(x, i, dim=axis))(r, idx, axis=1))
        y = y * r_sel.reshape(B, C, 1)
        b_off = (torch.arange(B) * S).reshape(B, 1)
        flat_idx = (idx + b_off).reshape(B * C)
        zero = (x * 0.0).reshape(B * S, D)
        upd = _scatter_add(zero, flat_idx, y.reshape(B * C, D), axis=0)
        return x + upd.reshape(B, S, D)

    x = A_u
    xn = _layernorm(x, axis=-1)
    s = _A_ref(xn, A_log_A_real, A_A_imag, A_C_real, A_C_imag, A_log_dt, A_D_skip)
    g = _silu(_B_ref(xn, B_w_r, B_w_gate, B_w_up, B_w_down))
    return x + s * g
```

```cpp
#include <cuda_runtime.h>
#include <cuda_bf16.h>
#include <cuda_fp16.h>
#include <cuda.h>
#include <stdint.h>

#define RM 112
#define RH 88
#define NSTG 6
#define ORD 0
#define FSB 1
#define RH2 RH
#define RF2 (480 - 2 * RM - 2 * RH2)
#define NOFIX 0
#define NFFN 112
namespace {

constexpr int RING = 8;
constexpr uint32_t BS = 272, TS8 = 8 * BS;
constexpr uint32_t O_RING = 0;
constexpr uint32_t O_XT   = RING * 8192;
constexpr uint32_t O_STG  = O_XT + 64;
constexpr uint32_t O_RAW  = O_XT + 17 * TS8;
constexpr uint32_t O_PRIV = O_RAW + 16 * TS8;
constexpr uint32_t PRIV   = 7760;
constexpr uint32_t P_TAB  = 4224;
constexpr uint32_t O_XSEL = O_PRIV + 8 * PRIV;
constexpr uint32_t O_MISC = O_XSEL + 4160;
constexpr uint32_t O_ROWS = (RING - 4) * 8192;
constexpr uint32_t O_PART = O_MISC;
constexpr uint32_t O_HX   = O_PART + 2048;
constexpr uint32_t O_HT   = O_HX + 256;
constexpr uint32_t O_SEL  = O_HT + 288;
constexpr uint32_t O_BAR  = O_SEL + 32;
constexpr uint32_t B_ROW = O_BAR, B_FULL = B_ROW + 16, B_H = B_FULL + 8 * 24, B_SEL = B_H + 8, B_P1 = B_SEL + 16,
                   B_X = B_P1 + 8, B_GO = B_X + 16, B_Y = B_GO + 24, B_RAW = B_Y + 64;
constexpr uint32_t SMEM_BYTES = B_Y + 96;
static_assert(B_Y - B_FULL == 11 * 24 && O_RAW % 128 == 0 && O_STG % 128 == 64, "layout");
static_assert(SMEM_BYTES <= 232448, "smem");
constexpr int T1 = 18, T4 = 561, T2 = 596, T3 = 756;

#define SCHED(X) X(0, ROW0, 300) X(1, ROW1, 1000) X(2, ROWD, 0) X(3, GAT0, 900) X(4, GAT1, 4400) X(5, GATD, 60) X(6, TGO0, 2700) \
    X(7, TTOP, 3800) X(8, W0, 1700) X(9, WD, 280) X(10, NPF, 10) X(11, PACE, 4) X(13, TFIX, 10300)
#define X(i, n, v) constexpr int n = v;

struct Scratch {
    uint2 stats[2 * 2048];
    uint2 keys[8 * 128];
    uint4 yp[64 * 64 * 8];
    unsigned epoch[128];
    int ts[128 * 128];
};
__device__ Scratch g_scratch;

struct Maps { CUtensorMap m[5]; };
struct Params {
    const uint4* u; const uint2* logA; const uint2* Aim; const uint2* Cre; const uint2* Cim;
    const uint16_t* logdt; const uint16_t* Dsk; const uint4* wr;
    uint4* out; Scratch* S; uint32_t zero;
};

#define DI __device__ __forceinline__
DI int lane_id() { int l; asm volatile("mov.u32 %0,%%laneid;" : "=r"(l)); __builtin_assume(l >= 0 && l < 32); return l; }
DI uint32_t pin(uint32_t v) { return __shfl_sync(~0u, v, lane_id()); }
DI int now_ns() { int c; asm volatile("mov.u32 %0,%%globaltimer_lo;" : "=r"(c)::"memory"); return c; }
DI void spin(int t) {
    asm volatile("{.reg .pred p; .reg .s32 c; L: mov.u32 c,%%globaltimer_lo; sub.s32 c,c,%0; setp.lt.s32 p,c,0; @p nanosleep.u32 32; @p bra.uni L;}" ::"r"(t) : "memory");
}
DI void mbar_arrive_e(uint32_t b) { asm volatile("{.reg .pred p; elect.sync _|p,0xffffffff; @p mbarrier.arrive.shared.b64 _,[%0];}" ::"r"(b) : "memory"); }
DI void mbar_expect_e(uint32_t b, int tx) { asm volatile("{.reg .pred p; elect.sync _|p,0xffffffff; @p mbarrier.arrive.expect_tx.shared.b64 _,[%0],%1;}" ::"r"(b), "r"(tx) : "memory"); }
DI void mbar_wait(uint32_t b) {
    asm volatile("{.reg .pred p; W: mbarrier.try_wait.parity.shared.b64 p,[%0],0; @!p bra.uni W; }" ::"r"(b) : "memory");
}
DI void bulk_e(uint32_t dst, const void* src, uint32_t bar, int bytes) {
    asm volatile("{.reg .pred p; elect.sync _|p,0xffffffff; @p cp.async.bulk.shared::cluster.global.mbarrier::complete_tx::bytes [%0],[%1],%3,[%2];}" ::"r"(dst), "l"(src), "r"(bar), "r"(bytes) : "memory");
}
DI void tma3d_e(uint32_t dst, const CUtensorMap* m, int c1, int c2, uint32_t bar) {
    asm volatile("{.reg .pred p; elect.sync _|p,0xffffffff; @p mbarrier.arrive.expect_tx.shared.b64 _,[%2],8192;\n"
                 "@p cp.async.bulk.tensor.3d.shared::cluster.global.mbarrier::complete_tx::bytes [%0],[%1,{0,%3,%4}],[%2];}" ::"r"(dst), "l"(m), "r"(bar), "r"(c1), "r"(c2) : "memory");
}
DI void tma4d_e(uint32_t dst, const CUtensorMap* m, int c0, int c3, uint32_t bar) {
    asm volatile("{.reg .pred p; elect.sync _|p,0xffffffff;\n"
                 "@p cp.async.bulk.tensor.4d.shared::cluster.global.mbarrier::complete_tx::bytes [%0],[%1,{%3,0,0,%4}],[%2];}" ::"r"(dst), "l"(m), "r"(bar), "r"(c0), "r"(c3) : "memory");
}
DI void tma4d_st_e(uint32_t src, const CUtensorMap* m, int c0, int c3) {
    asm volatile("{.reg .pred p; elect.sync _|p,0xffffffff; @p cp.async.bulk.tensor.4d.global.shared::cta.bulk_group [%1,{%2,0,0,%3}],[%0];}" ::"r"(src), "l"(m), "r"(c0), "r"(c3) : "memory");
}
DI void st_async(uint32_t dst, const uint4& v, uint32_t bar) {
    asm volatile("st.async.shared::cluster.mbarrier::complete_tx::bytes.v4.b32 [%0],{%1,%2,%3,%4},[%5];" ::"r"(dst), "r"(v.x), "r"(v.y), "r"(v.z), "r"(v.w), "r"(bar) : "memory");
}
DI void fence_async() { asm volatile("fence.proxy.async.shared::cta;" ::: "memory"); }
DI void bar_sync(int id, int n) { asm volatile("bar.sync %0,%1;" ::"r"(id), "r"(n) : "memory"); }
DI void bar_arrive(int id, int n) { asm volatile("bar.arrive %0,%1;" ::"r"(id), "r"(n) : "memory"); }
DI uint4 ldg128(const void* p) { uint4 v; asm volatile("ld.global.nc.v4.u32 {%0,%1,%2,%3},[%4];" : "=r"(v.x), "=r"(v.y), "=r"(v.z), "=r"(v.w) : "l"(p) : "memory"); return v; }
DI uint2 ldg64(const void* p) { uint2 v; asm volatile("ld.global.nc.v2.u32 {%0,%1},[%2];" : "=r"(v.x), "=r"(v.y) : "l"(p) : "memory"); return v; }
DI uint4 ldr128(const void* p) {
    uint4 v;
    asm volatile("{.reg .b128 t; .reg .b64 a,b; ld.relaxed.gpu.global.b128 t,[%4]; mov.b128 {a,b},t; mov.b64 {%0,%1},a; mov.b64 {%2,%3},b;}"
                 : "=r"(v.x), "=r"(v.y), "=r"(v.z), "=r"(v.w) : "l"(p) : "memory");
    return v;
}
DI uint2 ldr64(const void* p) { uint2 v; asm volatile("{.reg .b64 t; ld.relaxed.gpu.global.b64 t,[%2]; mov.b64 {%0,%1},t;}" : "=r"(v.x), "=r"(v.y) : "l"(p) : "memory"); return v; }
DI void str64(void* p, uint32_t x, uint32_t y) { asm volatile("{.reg .b64 t; mov.b64 t,{%1,%2}; st.relaxed.gpu.global.b64 [%0],t;}" ::"l"(p), "r"(x), "r"(y) : "memory"); }
DI void str128(void* p, uint4 v) {
    asm volatile("{.reg .b128 t; .reg .b64 a,b; mov.b64 a,{%1,%2}; mov.b64 b,{%3,%4}; mov.b128 t,{a,b}; st.relaxed.gpu.global.b128 [%0],t;}" ::"l"(p), "r"(v.x), "r"(v.y), "r"(v.z), "r"(v.w) : "memory");
}
DI uint32_t lds32(uint32_t a) { uint32_t v; asm volatile("ld.shared.u32 %0,[%1];" : "=r"(v) : "r"(a) : "memory"); return v; }
DI uint32_t lds16(uint32_t a) { uint32_t v; asm volatile("ld.shared.u16 %0,[%1];" : "=r"(v) : "r"(a) : "memory"); return v; }
DI uint2 lds64(uint32_t a) { uint2 v; asm volatile("ld.shared.v2.u32 {%0,%1},[%2];" : "=r"(v.x), "=r"(v.y) : "r"(a) : "memory"); return v; }
DI uint4 lds128(uint32_t a) { uint4 v; asm volatile("ld.shared.v4.u32 {%0,%1,%2,%3},[%4];" : "=r"(v.x), "=r"(v.y), "=r"(v.z), "=r"(v.w) : "r"(a) : "memory"); return v; }
DI void sts16(uint32_t a, uint32_t v) { asm volatile("st.shared.u16 [%0],%1;" ::"r"(a), "r"(v) : "memory"); }
DI void sts32(uint32_t a, uint32_t v) { asm volatile("st.shared.u32 [%0],%1;" ::"r"(a), "r"(v) : "memory"); }
DI void sts64(uint32_t a, uint32_t x, uint32_t y) { asm volatile("st.shared.v2.u32 [%0],{%1,%2};" ::"r"(a), "r"(x), "r"(y) : "memory"); }
DI void sts128(uint32_t a, uint32_t x, uint32_t y, uint32_t z, uint32_t w) { asm volatile("st.shared.v4.u32 [%0],{%1,%2,%3,%4};" ::"r"(a), "r"(x), "r"(y), "r"(z), "r"(w) : "memory"); }
DI uint4 ldsm4(uint32_t a) { uint4 v; asm volatile("ldmatrix.sync.aligned.m8n8.x4.shared.b16 {%0,%1,%2,%3},[%4];" : "=r"(v.x), "=r"(v.y), "=r"(v.z), "=r"(v.w) : "r"(a) : "memory"); return v; }
DI uint4 ldsm4t(uint32_t a) { uint4 v; asm volatile("ldmatrix.sync.aligned.m8n8.x4.trans.shared.b16 {%0,%1,%2,%3},[%4];" : "=r"(v.x), "=r"(v.y), "=r"(v.z), "=r"(v.w) : "r"(a) : "memory"); return v; }
DI void stsm4(uint32_t a, uint32_t x, uint32_t y, uint32_t z, uint32_t w) { asm volatile("stmatrix.sync.aligned.m8n8.x4.shared.b16 [%0],{%1,%2,%3,%4};" ::"r"(a), "r"(x), "r"(y), "r"(z), "r"(w) : "memory"); }
DI void stsm4t(uint32_t a, uint32_t x, uint32_t y, uint32_t z, uint32_t w) { asm volatile("stmatrix.sync.aligned.m8n8.x4.trans.shared.b16 [%0],{%1,%2,%3,%4};" ::"r"(a), "r"(x), "r"(y), "r"(z), "r"(w) : "memory"); }
DI void mma_bf(float (&d)[4], uint32_t a0, uint32_t a1, uint32_t a2, uint32_t a3, uint32_t b0, uint32_t b1) {
    asm("mma.sync.aligned.m16n8k16.row.col.f32.bf16.bf16.f32 {%0,%1,%2,%3},{%4,%5,%6,%7},{%8,%9},{%0,%1,%2,%3};"
        : "+f"(d[0]), "+f"(d[1]), "+f"(d[2]), "+f"(d[3]) : "r"(a0), "r"(a1), "r"(a2), "r"(a3), "r"(b0), "r"(b1));
}
DI void mma_bf(float (&d)[4], const uint4& a, uint32_t b0, uint32_t b1) { mma_bf(d, a.x, a.y, a.z, a.w, b0, b1); }
typedef uint32_t h4[2];
DI void mma_h(h4& d, const uint4& a, uint32_t b0, uint32_t b1) {
    asm("mma.sync.aligned.m16n8k16.row.col.f16.f16.f16.f16 {%0,%1},{%2,%3,%4,%5},{%6,%7},{%0,%1};"
        : "+r"(d[0]), "+r"(d[1]) : "r"(a.x), "r"(a.y), "r"(a.z), "r"(a.w), "r"(b0), "r"(b1));
}
DI void mma_k8(h4& d, uint32_t a0, uint32_t a1, uint32_t b0) {
    asm("mma.sync.aligned.m16n8k8.row.col.f16.f16.f16.f16 {%0,%1},{%2,%3},{%4},{%0,%1};" : "+r"(d[0]), "+r"(d[1]) : "r"(a0), "r"(a1), "r"(b0));
}
DI void mma_cvt(float (&d)[4], const h4& a, uint32_t b) {
    asm("mma.sync.aligned.m16n8k8.row.col.f32.f16.f16.f32 {%0,%1,%2,%3},{%4,%5},{%6},{%7,%7,%7,%7};"
        : "=f"(d[0]), "=f"(d[1]), "=f"(d[2]), "=f"(d[3]) : "r"(a[0]), "r"(a[1]), "r"(b), "f"(0.f));
}
DI uint32_t pk_bf(float lo, float hi) { uint32_t r; asm("cvt.rn.bf16x2.f32 %0,%1,%2;" : "=r"(r) : "f"(hi), "f"(lo)); return r; }
DI uint32_t pk_h(float lo, float hi) { uint32_t r; asm("cvt.rn.f16x2.f32 %0,%1,%2;" : "=r"(r) : "f"(hi), "f"(lo)); return r; }
DI float bf_lo(uint32_t v) { return __uint_as_float(v << 16); }
DI float bf_hi(uint32_t v) { return __uint_as_float(v & 0xffff0000u); }
DI float bfr(float x) { return bf_lo(pk_bf(x, 0.f)); }
DI uint32_t hadd(uint32_t a, uint32_t b) { uint32_t r; asm("add.rn.f16x2 %0,%1,%2;" : "=r"(r) : "r"(a), "r"(b)); return r; }
DI uint32_t hscl(uint32_t a) { uint32_t r; asm("mul.rn.f16x2 %0,%1,%2;" : "=r"(r) : "r"(a), "r"(0x02000200)); return r; }
DI uint32_t bsub_lo(uint32_t x, uint32_t m) { uint32_t r; asm("{.reg .b16 l,h; .reg .b32 t; mov.b32 {l,h},%2; mov.b32 t,{l,l}; sub.rn.bf16x2 %0,%1,t;}" : "=r"(r) : "r"(x), "r"(m)); return r; }
DI uint32_t bmul(uint32_t a, uint32_t b) { uint32_t r; asm("mul.rn.bf16x2 %0,%1,%2;" : "=r"(r) : "r"(a), "r"(b)); return r; }
DI uint32_t bfma(uint32_t a, uint32_t b, uint32_t c) { uint32_t r; asm("fma.rn.bf16x2 %0,%1,%2,%3;" : "=r"(r) : "r"(a), "r"(b), "r"(c)); return r; }
DI uint32_t norm2(uint32_t x, uint32_t m, uint32_t r) {
    uint32_t o;
    asm("{.reg .b16 l,h; .reg .b32 t,e; mov.b32 {l,h},%2; mov.b32 t,{h,h}; mul.rn.bf16x2 e,%1,t; mov.b32 t,{l,l}; fma.rn.bf16x2 %0,%1,t,e;}" : "=r"(o) : "r"(bsub_lo(x, m)), "r"(r));
    return o;
}
DI float ex2(float x) { float r; asm("ex2.approx.ftz.f32 %0,%1;" : "=f"(r) : "f"(x)); return r; }
DI float rcp(float x) { float r; asm("rcp.approx.ftz.f32 %0,%1;" : "=f"(r) : "f"(x)); return r; }
DI float ftanh(float x) { float r; asm("tanh.approx.f32 %0,%1;" : "=f"(r) : "f"(x)); return r; }
DI float fsqrt(float x) { float r; asm("sqrt.approx.ftz.f32 %0,%1;" : "=f"(r) : "f"(x)); return r; }
constexpr float LOG2E = 1.4426950408889634f;
DI float sigm(float x) { return rcp(1.f + ex2(-LOG2E * x)); }
DI float silu(float x) { return x * sigm(x); }
struct cf { float r, i; };
DI cf cmul(cf a, cf b) { return {fmaf(a.r, b.r, -a.i * b.i), fmaf(a.r, b.i, a.i * b.r)}; }
DI float mul2(float a, float b) { float r; asm("{.reg .f32 t; mul.f32 t,%1,%2; mul.f32 %0,t,0f40000000;}" : "=f"(r) : "f"(a), "f"(b)); return r; }
DI cf csq(cf a) { return {fmaf(a.r, a.r, -a.i * a.i), mul2(a.r, a.i)}; }
DI cf csqc(cf a) { return {fmaf(a.r, a.r, -a.i * a.i), mul2(a.r, -a.i)}; }
DI cf cexp(float a2, float be, float p) { float m = ex2(a2 * p); float t = be * p; return {m * __cosf(t), m * __sinf(t)}; }

struct ch2 { uint32_t r, i; };
template <int V>
DI ch2 hmul(ch2 a, uint32_t fr, uint32_t fi) {
    ch2 o;
    if (V) asm("{.reg .b32 t,u; mul.rn.f16x2 t,%3,%5; neg.f16x2 t,t; mul.rn.f16x2 u,%2,%5; fma.rn.f16x2 %0,%2,%4,t; fma.rn.f16x2 %1,%3,%4,u;}"
               : "=&r"(o.r), "=r"(o.i) : "r"(a.r), "r"(a.i), "r"(fr), "r"(fi));
    else asm("{.reg .b32 t,u,n; mul.rn.f16x2 t,%2,%4; mul.rn.f16x2 u,%3,%4; neg.f16x2 n,%3; fma.rn.f16x2 %0,n,%5,t; fma.rn.f16x2 %1,%2,%5,u;}"
             : "=&r"(o.r), "=r"(o.i) : "r"(a.r), "r"(a.i), "r"(fr), "r"(fi));
    return o;
}
DI ch2 hmul(ch2 a, uint32_t f) {
    ch2 o;
    asm("{.reg .b32 t,u,x,y; .reg .b16 l,h; mov.b32 {l,h},%4; mov.b32 x,{l,l}; mov.b32 y,{h,h};\n"
        "mul.rn.f16x2 t,%3,y; neg.f16x2 t,t; fma.rn.f16x2 %0,%2,x,t; mul.rn.f16x2 u,%3,x; fma.rn.f16x2 %1,%2,y,u;}"
        : "=&r"(o.r), "=r"(o.i) : "r"(a.r), "r"(a.i), "r"(f));
    return o;
}
DI uint32_t pk_h(cf f) { return pk_h(f.r, f.i); }
DI void sts_ch2(uint32_t a, ch2 x, ch2 y, ch2 z, ch2 w) { sts128(a, x.r, y.r, z.r, w.r); sts128(a + 512, x.i, y.i, z.i, w.i); }

#define TDUMP
#define TS(i)
#define TV(i, v)
#define T2S(i)

DI uint4 toep(uint32_t a, uint32_t Z) {
    uint4 r; r.x = lds32(a); r.y = lds32(a + 32); r.z = lds32(a - 32); r.w = r.x ^ Z;
    return r;
}
DI void sched_fence(uint32_t Z) { asm volatile("{.reg .pred p; setp.ne.u32 p,%0,0; @p griddepcontrol.launch_dependents;}" ::"r"(Z) : "memory"); }
DI uint32_t copy(uint32_t v, uint32_t Z) { uint32_t r; asm volatile("xor.b32 %0,%1,%2;" : "=r"(r) : "r"(v), "r"(Z)); return r; }
DI void pin4(uint32_t& a, uint32_t& b, uint32_t& c, uint32_t& d, uint32_t Z) {
    asm volatile("{.reg .pred p; setp.ne.u32 p,%4,0; @p ld.shared.v4.u32 {%0,%1,%2,%3},[%4];}" : "+r"(a), "+r"(b), "+r"(c), "+r"(d) : "r"(Z) : "memory");
}

#define BFRAG(B, s) ((s) & 1) ? B[(s) >> 1].z : B[(s) >> 1].x, ((s) & 1) ? B[(s) >> 1].w : B[(s) >> 1].y
DI uint32_t comp(const uint4& v, int k) { return k == 0 ? v.x : k == 1 ? v.y : k == 2 ? v.z : v.w; }
template <bool FIRST>
DI void conv_half(h4 (&acc)[16], uint32_t aA, uint32_t aB, uint32_t bar, uint32_t Z) {
    constexpr int O = FIRST ? 0 : 8;
    uint4 A[4], B[4], A2[4], B2[4], A64;
#pragma unroll
    for (int i = 0; i < 4; i++) A[i] = toep(aA + 7 * 64 + i * 512, Z);
    if (FIRST && !ORD)
#pragma unroll
        for (int i = 0; i < 4; i++) pin4(A[i].x, A[i].y, A[i].z, A[i].w, Z);
    if (!ORD) mbar_wait(bar);
#pragma unroll
    for (int i = 0; i < 4; i++) B[i] = ldsm4(aB - 7 * BS + i * 2 * TS8);
    auto step = [&](const uint4*, const uint4* b, uint4*, uint4* bn, int j, bool first = false) {
#pragma unroll
        for (int i = 3; i >= 0; i--) {
            if (i == 3 ? !first : i == 1 && j)
#pragma unroll
                for (int k = 4 - i; k >= 3 - i; k--) {
                    const uint32_t a = aA + (j == 0 ? 6 : i == 3 ? j + 1 : j) * 64 + k * 512;
                    A[k].y = copy(A[k].z, Z); A[k].x = lds32(a); A[k].z = lds32(a - 32);
                }
            if (j && i == 2)
#pragma unroll
                for (int k = 0; k < 4; k++) bn[k] = ldsm4(aB - j * BS + k * 2 * TS8);
#pragma unroll
            for (int s = 0; s < 8; s++) {
                if (FIRST || s + i < 8) mma_h(acc[O + s + i], A[i], BFRAG(b, s));
                if (s == 3 && (i & 1) == 0) sched_fence(Z);
            }
            if (i == 2 ? !first : i == 0 && j) { A[3 - i].w = copy(A[3 - i].x, Z); A[2 - i].w = copy(A[2 - i].x, Z); }
            sched_fence(Z);
        }
    };
    step(A, B, A2, B2, 6, true);
#pragma unroll 1
    for (int n = 0; n < 3; n++) {
        step(A2, B2, A, B, 5);
        step(A, B, A2, B2, 4);
        aA -= 128; aB += 2 * BS;
    }
    if (ORD && FIRST) mbar_wait(bar + 8);
    const uint4 A32 = toep(aA + 384 + 2048, Z);
    if (FIRST) A64 = toep(aA + 384 + (T4 - T1) * 4, Z);
    const uint4 Y = make_uint4(A32.y ^ Z, A32.y & Z, FIRST ? A64.y ^ Z : 0, FIRST ? A64.y & Z : 0);
    step(A2, B2, A, B, 0);
    if (FIRST) {
#pragma unroll
        for (int s = 7; s >= 0; s--) mma_h(acc[s + 8], A64, BFRAG(B2, s));
#pragma unroll
        for (int s = 7; s >= 0; s--) mma_k8(acc[s + 8], Y.z, Y.w, comp(B[s >> 1], (s & 1) * 2 + 1));
    }
#pragma unroll
    for (int s = 0; s < (FIRST ? 8 : 4); s++) mma_h(acc[O + s + 4], A32, BFRAG(B2, s));
#pragma unroll
    for (int s = 0; s < (FIRST ? 8 : 4); s++) mma_k8(acc[O + s + 4], Y.x, Y.y, comp(B[s >> 1], (s & 1) * 2 + 1));
}

__global__ void __cluster_dims__(2, 1, 1) __launch_bounds__(640, 1)
fused_kernel(const __grid_constant__ Params prm, const __grid_constant__ Maps maps) {
    const CUtensorMap &mg = maps.m[0], &md = maps.m[2], &mx = maps.m[3], &mo = maps.m[4];
    extern __shared__ __align__(1024) unsigned char smem_raw[];
    SCHED(X)
    const uint32_t tid = threadIdx.x;
    uint2 vA, vI, vR, vC;
    uint32_t ldt, Dsk;
    if (tid < 256) {
        const int e = blockIdx.x * 256 + tid;
        vA = ldg64(prm.logA + e); vI = ldg64(prm.Aim + e); vR = ldg64(prm.Cre + e); vC = ldg64(prm.Cim + e);
        ldt = prm.logdt[e >> 5]; Dsk = prm.Dsk[e >> 5];
    }
    const int t0 = __shfl_sync(~0u, now_ns() + (threadIdx.x >> 10), 0);
    const uint32_t sb = (uint32_t)__cvta_generic_to_shared(smem_raw);
    const int b = blockIdx.x, rk = b & 1, q = b >> 1;
    const int w = __shfl_sync(~0u, tid >> 5, 0);
#define LANES const int lane = lane_id(), g = lane >> 2, c = lane & 3, mi = lane >> 3, r8 = lane & 7; (void)g; (void)c; (void)mi; (void)r8
    uint32_t pb;
    asm("mapa.shared::cluster.u32 %0,%1,%2;" : "=r"(pb) : "r"(sb), "r"(rk ^ 1));
    if (w < 17) asm volatile("barrier.cluster.arrive.relaxed.aligned;" ::: "memory");
    const uint32_t Z = prm.zero;
    if (w == 16) {
        asm volatile("{.reg .pred p; elect.sync _|p,0xffffffff; @p mbarrier.init.shared.b64 [%0],1; @p mbarrier.init.shared.b64 [%0+8],1; fence.mbarrier_init.release.cluster;\n"
                     "@p mbarrier.arrive.expect_tx.shared.b64 _,[%0],16384; @p mbarrier.arrive.expect_tx.shared.b64 _,[%0+8],16384;}" ::"r"(sb + B_ROW) : "memory");
        if (ROW0) spin(t0 + ROW0);
        bulk_e(sb + O_ROWS, prm.u + b * 1024, sb + B_ROW, 16384);
        TS(6);
    }

    if (w < 8) {
        LANES;
        const uint32_t pv = sb + O_PRIV + w * PRIV, tb = pv + P_TAB, rw = sb + O_RAW + w * 32;
        const uint32_t st = pv + lane * 16;
        uint32_t cyP = pv + 528 + c * 1056 + mi * 4;
        sts64(rw - TS8 + g * BS + c * 8, 0, 0);
        h4 kd[6] = {};
        const uint32_t lA = pv + (mi >> 1) * 512 + (mi & 1) * 128 + r8 * 16, lB = pv + (2 + mi) * 512 + r8 * 16;
        const uint32_t lC = pv + (6 + (mi & 1)) * 512 + (mi >> 1) * 128 + r8 * 16, lF = pv + 4096 + (mi & 1) * 64 + (mi >> 1) * 16;
        const uint32_t sF = pv + 4096 + lane * 2;
        bar_sync(6, 288);
        asm volatile("setmaxnreg.inc.sync.aligned.u32 %0;" ::"n"(RM));
        const float dt = bfr(ex2(bf_lo(ldt + (lane & Z)) * LOG2E));
        uint32_t mx2 = __vmaxu2(__vmaxu2(vR.x & 0x7fff7fffu, vR.y & 0x7fff7fffu), __vmaxu2(vC.x & 0x7fff7fffu, vC.y & 0x7fff7fffu));
        const int ex = min(max(max((int)((__reduce_max_sync(~0u, max(mx2 >> 16, mx2 & 0xffffu)) >> 7) + (__float_as_uint(dt) >> 23)), (int)((Dsk >> 7) & 255) + 108), 140), 370);
        const float cs = dt * __uint_as_float((387 - ex) << 23), dl = -dt * LOG2E, ncs = __uint_as_float(__float_as_uint(cs) ^ 0x80000000u ^ Z);
        TS(w == 0 ? 0 : 63); T2S(0);
        auto gen = [&](uint32_t sel) {
            const float a2 = bfr(ex2(__uint_as_float(__byte_perm(vA.x, vA.y, sel) & 0xffff0000u) * LOG2E)) * dl;
            const float be = __uint_as_float(__byte_perm(vI.x, vI.y, sel) & 0xffff0000u) * dt;
            const cf wv = {__uint_as_float(__byte_perm(vR.x, vR.y, sel) & 0xffff0000u) * cs, __uint_as_float(__byte_perm(vC.x, vC.y, sel) & 0xffff0000u) * ncs};
            const cf y1 = cexp(a2, -be, 1.f), y2 = csq(y1), y4 = csq(y2), z8 = csqc(y4), z16 = csq(z8), z32 = csq(z16);
            const cf z64 = cexp(a2, be, 64.f);
            {
                const uint32_t f = pk_h(z64) ^ Z, f16 = pk_h(z16);
                const ch2 m0 = {pk_h(1.f, z32.r), pk_h(0.f, z32.i)}, m1 = hmul(m0, pk_h(z8));
                sts_ch2(st, m0, m1, hmul(m0, f16), hmul(m1, f16));
                sts16(sF, f); sts16(sF + 64, f >> 16);
            }
            {
                const cf w4 = cmul(wv, y4), y256 = csqc(csq(z64)), y512 = csq(y256);
                const uint32_t f2 = pk_h(y2), f256 = pk_h(y256), f512 = pk_h(y512);
                const ch2 p0 = {pk_h(wv.r, w4.r), pk_h(wv.i, w4.i)};
                const ch2 p1 = hmul(p0, pk_h(y1)), p2 = hmul(p0, f2), p4 = hmul(p0, pk_h(y4));
                sts_ch2(st + 1024, p1, p2, hmul(p1, f2), p4);
                const ch2 e1 = hmul(p4, f256);
                sts_ch2(st + 2048, hmul(p2, f256), e1, hmul(p4, f512), hmul(e1, f512));
                const ch2 g0 = {__byte_perm(p4.r, e1.r, 0x7632), __byte_perm(p4.i, e1.i, 0x7632)}, s0 = hmul(g0, pk_h(csq(y512)));
                sts_ch2(st + 3072, s0, hmul(s0, f512), p0, g0);
            }
            __syncwarp();
        };
        auto mul = [&]() {
#pragma unroll
            for (int k2 = 0; k2 < 2; k2++) {
                const uint4 M = ldsm4t(lA + k2 * 256), F = ldsm4(lF + k2 * 32);
                uint4 B[3];
                B[0] = ldsm4t(lB + k2 * 256); B[1] = ldsm4t(lB + k2 * 256 + 128); B[2] = ldsm4t(lC + k2 * 256);
#pragma unroll
                for (int i = 1; i >= 0; i--) {
                    const uint32_t fr = i ? F.z : F.x, fi = i ? F.w : F.y;
                    const ch2 m0 = {i ? M.y ^ Z : M.x, i ? M.w ^ Z : M.z}, m1 = hmul<1>(m0, fr, fi), m2 = hmul<0>(m1, fr, fi), m3 = hmul<1>(m2, fr, fi);
                    const uint4 A0 = make_uint4(m0.r, m1.r, m0.i, m1.i), A1 = make_uint4(m2.r, m3.r, m2.i, m3.i);
                    mma_h(kd[0], A0, B[i].x, B[i].y); mma_h(kd[1], A0, B[i].z, B[i].w); mma_h(kd[2], A0, i ? B[2].z : B[2].x, i ? B[2].w : B[2].y);
                    mma_h(kd[3], A1, B[i].x, B[i].y); mma_h(kd[4], A1, B[i].z, B[i].w); mma_h(kd[5], A1, i ? B[2].z : B[2].x, i ? B[2].w : B[2].y);
                }
            }
            __syncwarp();
        };
        gen(0x1044);
#pragma unroll 1
        for (uint32_t sel = 0x3244; sel < 0x8000; sel += 0x2200) {
            mul();
            gen(sel);
        }
        mul();
        TS(w == 0 ? 59 : w == 4 ? 60 : 63); T2S(1);
        {
#pragma unroll
            for (int nt = 0; nt < 3; nt++) stsm4(pv + (mi * 8 + (r8 >> 1) + (r8 & 1) * 4) * 16 + nt * 1056, kd[nt][0], kd[nt][1], kd[nt + 3][0], kd[nt + 3][1]);
            sts128(st + (lane < 4 ? P_TAB : P_TAB + (T1 + 518 - 16) * 4), 0, 0, 0, 0);
            sts32(cyP + 512, 0);
            __syncwarp();
            uint4 R0 = lds128(st), R1 = lds128(st + 1056), R2 = lds128(st + 2112);
            R0.x = hscl(R0.x); R0.y = hscl(R0.y); R0.z = hscl(R0.z); R0.w = hscl(R0.w);
            R1.x = hscl(R1.x); R1.y = hscl(R1.y); R1.z = hscl(R1.z); R1.w = hscl(R1.w);
            R2.x = hscl(R2.x); R2.y = hscl(R2.y); R2.z = hadd(hscl(R2.z), pk_h(bf_lo(Dsk) * __uint_as_float((371 - ex) << 23), 0.f));
            const bool l31 = lane == 31, l2 = lane < 2;
            uint32_t nx = __shfl_down_sync(~0u, R0.x, 1);
            if (l31) nx = R0.w >> 16;
            const uint32_t pr = __shfl_sync(~0u, l31 ? R0.w : R1.y, lane - 1);
            const uint32_t sA = __shfl_sync(~0u, R1.z, lane - 2), sB = __shfl_sync(~0u, R1.w, lane - 2);
            const uint32_t s0 = __shfl_sync(~0u, R2.x, lane - 2), s1 = __shfl_sync(~0u, R2.y, lane - 2);
            uint32_t a = tb + lane * 32;
            sts128(a + (T1 + 2) * 4, __byte_perm(R0.y, R0.x, 0x5410), __byte_perm(R0.z, R0.y, 0x5410), __byte_perm(R0.w, R0.z, 0x5410), __byte_perm(R0.x, R0.w, 0x5432));
            sts128(a + (T1 + 6) * 4, __byte_perm(R0.y, R0.x, 0x7632), __byte_perm(R0.z, R0.y, 0x7632), __byte_perm(R0.w, R0.z, 0x7632), __byte_perm(R0.w, nx, 0x3254));
            const uint32_t d1 = __byte_perm(R1.y, 0, 0x1010), d3 = __byte_perm(R1.y, 0, 0x3232);
            sts128(a + (T1 + 258) * 4, __byte_perm(pr, R1.x, 0x3254), __byte_perm(R1.y, R1.x, 0x5410), d1, d1);
            sts128(a + (T1 + 262) * 4, __byte_perm(R1.x, R1.y, 0x5432), __byte_perm(R1.y, R1.x, 0x7632), d3, d3);
            a = tb + T2 * 4 + (lane & 1) * 320 + (lane >> 1) * 8;
            const uint32_t pA = l2 ? 0 : sA, pB = l2 ? sA : sB, pT = l2 ? sB : 0;
            sts64(a, __byte_perm(R1.z, pA, 0x5410), __byte_perm(R1.z, pA, 0x7632));
            sts64(a + 128, __byte_perm(R1.w, pB, 0x5410), __byte_perm(R1.w, pB, 0x7632));
            if (lane < 16) sts64(a + 256, pT << 16, pT & 0xffff0000u);
            a = tb + T3 * 4 + lane * 4;
            const uint32_t p0 = __byte_perm(0, s0, l2 ? 0x5432 : 0x7654), p1 = __byte_perm(s0, s1, l2 ? 0x5432 : 0x7654);
            sts32(a, __byte_perm(R2.x, p0, 0x5410)); sts32(a + 128, __byte_perm(R2.x, p0, 0x7632));
            sts32(a + 256, __byte_perm(R2.y, p1, 0x5410)); sts32(a + 384, __byte_perm(R2.y, p1, 0x7632));
            if (lane == 0) sts128(tb + (T1 - 2) * 4, 0, 0, R2.z & 0xffffu, __byte_perm(R0.x, R2.z, 0x5410));
            if (l31) {
                sts128(tb + (T1 + 514) * 4, d3, d3 << 16, 0, 0);
                sts128(tb + (T4 + 3) * 4, R1.w >> 16, __byte_perm(R1.w, 0, 0x3232), R1.w & 0xffff0000u, 0);
            }
        }
        __syncwarp();
        TS(w == 0 ? 1 : 63); T2S(9);
        h4 acc[16] = {};
        const uint32_t dd = g - 2 * c;
        uint32_t a1 = tb + T1 * 4 + dd * 4, t2 = tb + T2 * 4 + dd * 8, aB = rw + r8 * BS + (mi >> 1) * TS8 + (mi & 1) * 16, ac0 = rw + lane * BS;
        uint32_t fa = pv + 16 + r8 * 16 + mi * 528, fb = fa + ((mi & 1) ? -528 : 512), fc = (mi < 2 ? fa : fb) + 4 * 528, fo = st + 16;
        uint32_t yb = sb + O_STG + 256 + w * 528 + (lane & 15) * 16, ya = (mi >> 1) == rk ? aB - TS8 : yb;
        uint32_t yc = pb + O_STG + r8 * 528 + w * 32 + (mi & 1) * 16 + (mi >> 1) * 2 * TS8, yd = pb + B_Y;
        uint32_t Id = (dd >> 1) ? 0 : 0x3c00 << (16 * (g & 1)), sc = (ex - 116) * 0x800080;
        yb += (mi >> 1) * 2 * TS8;
        pin4(a1, t2, aB, ac0, Z); pin4(fa, fb, fc, cyP, Z); pin4(yc, yd, ya, yb, Z);
        uint32_t Zr = Z;
        pin4(fo, Zr, Id, sc, Z);
        const uint32_t t3 = t2 + (T3 - T2) * 4;
        auto put_tiles = [&](int p) {
#pragma unroll
            for (int k = 0; k < 2; k++) {
                float d[4], e[4];
                mma_cvt(d, acc[4 * p + 2 * k], Id);
                mma_cvt(e, acc[4 * p + 2 * k + 1], Id);
                stsm4t(ya + (4 * p + 2 * k) * TS8, bmul(pk_bf(d[0], d[1]), sc), bmul(pk_bf(d[2], d[3]), sc), bmul(pk_bf(e[0], e[1]), sc), bmul(pk_bf(e[2], e[3]), sc));
            }
            __syncwarp();
            st_async(yc, lds128(yb + p * 4 * TS8), yd);
            yc += 4 * TS8; yd += 8;
            mbar_expect_e(sb + B_Y + p * 8, 512);
        };
        auto filter = [&](int p) {
            const uint32_t ac = ac0 + p * 4 * TS8;
            const uint4 q2 = lds128(ac), q3 = lds128(ac + 16);
            const uint32_t cy = lds32(cyP + 512);
            const uint2 q0 = lds64(ac - BS + 8);
            const uint4 q1 = lds128(ac - BS + 16);
            __syncwarp();
            if (!ORD || p == 2) put_tiles(p);
            sts32(cyP, cy);
            const uint32_t U[13] = {q0.x, q0.y, q1.x, q1.y, q1.z, q1.w, q2.x, q2.y, q2.z, q2.w, q3.x, q3.y, q3.z};
            uint32_t Q[13], Pp[12], P4[12], C3[12], C5[10];
#pragma unroll
            for (int k = 1; k < 13; k++) Q[k] = __byte_perm(U[k - 1], U[k], 0x5432);
#pragma unroll
            for (int k = 1; k < 12; k++) Pp[k] = hadd(U[k], Q[k]);
#pragma unroll
            for (int k = 2; k < 12; k++) P4[k] = hadd(Pp[k], Pp[k - 1]);
#pragma unroll
            for (int k = 3; k < 12; k++) C3[k] = hadd(Pp[k], Q[k + 1]);
#pragma unroll
            for (int k = 1; k < 10; k++) C5[k] = hadd(P4[k + 1], U[k - 1]);
            if (p < 2)
#pragma unroll
                for (int h = 0; h < 2; h++) {
                    const int k = 2 + 4 * h;
                    sts128(fo + (4 + h) * 528, hadd(P4[k], C3[k + 1]), hadd(P4[k + 1], C3[k + 2]), hadd(P4[k + 2], C3[k + 3]), hadd(P4[k + 3], C3[k + 4]));
                    sts128(fo + (6 + h) * 528, hadd(P4[k + 2], C5[k - 1]), hadd(P4[k + 3], C5[k]), hadd(P4[k + 4], C5[k + 1]), hadd(P4[k + 5], C5[k + 2]));
                }
            sts128(fo, C3[4], C3[5], C3[6], C3[7]); sts128(fo + 528, C3[8], C3[9], C3[10], C3[11]);
            sts128(fo + 2 * 528, C5[2], C5[3], C5[4], C5[5]); sts128(fo + 3 * 528, C5[6], C5[7], C5[8], C5[9]);
            __syncwarp();
        };
        uint2 T[5], U2[5], V[8];
        auto coarse = [&](int p, bool load) {
            if (load)
#pragma unroll
                for (int D = 0; D < 5; D++) if (p < 2 || D < 4) T[D] = lds64(t2 + D * 64);
#pragma unroll
            for (int gl = 0; gl < 4; gl++) {
                const uint4 A = ldsm4t(fa + gl * 128);
#pragma unroll
                for (int D = 0; D < 5; D++) if (4 * p + gl + D + 4 < 16) mma_h(acc[4 * p + gl + D + 4], A, T[D].x, T[D].y);
            }
            if (load) {
#pragma unroll
                for (int D = 0; D < 5; D++) if (p < 2 || D < 4) U2[D] = lds64(t2 + 320 + D * 64);
#pragma unroll
                for (int D = 0; D < 8 - 4 * p; D++) V[D] = lds64(t3 + D * 64);
            }
#pragma unroll
            for (int gl = 0; gl < 4; gl++) {
                const uint4 A = ldsm4t(fb + gl * 128);
#pragma unroll
                for (int D = 0; D < 5; D++) if (4 * p + gl + D + 4 < 16) mma_h(acc[4 * p + gl + D + 4], A, U2[D].x, U2[D].y);
                if (p < 2) {
                    const uint4 A3 = ldsm4t(fc + gl * 128);
#pragma unroll
                    for (int D = 7; D >= 0; D--) if (4 * p + gl + D + 8 < 16) mma_h(acc[4 * p + gl + D + 8], A3, V[D].x, V[D].y);
                }
            }
        };
        T2S(10);
        if (!ORD) conv_half<true>(acc, a1, aB, sb + B_RAW, Zr);
        else mbar_wait(sb + B_RAW);
        T2S(11);
        filter(0);
        coarse(0, true);
        filter(1);
        coarse(1, false);
        T2S(12);
        if (ORD) {
            conv_half<true>(acc, a1, aB, sb + B_RAW, Zr);
            __syncwarp();
            put_tiles(0);
            put_tiles(1);
        }
        T2S(22);
        conv_half<false>(acc, a1, aB + 8 * TS8, sb + B_RAW + 8, Zr);
        T2S(23);
        filter(2);
        coarse(2, true);
        put_tiles(3);
        T2S(24);
        TS(w == 0 ? 3 : (w == 7 ? 4 : 63));
        TDUMP;
    } else if (w < 16) {
        LANES;
        const int hw = w - 8, n0 = 8 * rk + hw;
        if (RH < 96) asm volatile("setmaxnreg.dec.sync.aligned.u32 %0;" ::"n"(RH));
        if (RH > 96) asm volatile("setmaxnreg.inc.sync.aligned.u32 %0;" ::"n"(RH));
        uint32_t tag;
        asm volatile("ld.relaxed.gpu.global.u32 %0,[%1];" : "=r"(tag) : "l"(prm.S->epoch + b) : "memory");
        tag = ~tag << 31;
        {
            uint32_t W[16];
#pragma unroll
            for (int k = 0; k < 4; k++) {
                const uint4 v = ldg128(prm.wr + hw * 16 + (k ^ (g & 1)) * 4 + c);
                W[4 * k] = v.x; W[4 * k + 1] = v.y; W[4 * k + 2] = v.z; W[4 * k + 3] = v.w;
            }
#pragma unroll
            for (int k = 0; k < 16; k++) if (g & 2) W[k] = 0x3f803f80u;
            const bool dg = mi == c, od = g & 1;
            uint32_t ra = sb + O_ROWS + g * 2048 + hw * 256 + od * 64 + c * 16;
            uint32_t pa = sb + O_XSEL + ((dg ? 0 : 8 + 4 * (g & 2)) + 2 * c + od) * 48 + hw * 4;
            TS(hw == 4 ? 22 : 63);
            bar_sync(3, 288);
#pragma unroll 1
            for (int hf = 0; hf < 2; hf++) {
                float d[4] = {}, e[4] = {};
                mbar_wait(sb + B_ROW + hf * 8);
                TS(hw == 4 ? (hf ? 23 : 58) : 63);
#pragma unroll
                for (int k = 0; k < 4; k++) {
                    const uint4 x = lds128((ra ^ ((k & 1) << 6)) + (k >> 1) * 128);
                    mma_bf(d, x.x ^ Z, W[4 * k], x.y ^ Z, W[4 * k + 1], x.x, x.y);
                    mma_bf(e, x.z ^ Z, W[4 * k + 2], x.w ^ Z, W[4 * k + 3], x.z, x.w);
                }
#define PICK2(e) (dg ? (od ? e[1] : e[0]) : (od ? e[3] : e[2]))
                sts32(pa, __float_as_uint(PICK2(d) + PICK2(e)));
                TS(hf ? 63 : 8 + hw);
                bar_arrive(1 + 3 * hf, 288);
                ra += 16384; pa += 1152;
            }
        }
        const uint32_t xa = sb + O_XT + hw * 512 + lane * 16;
        const bool ownr = ((r8 >> 1) & 1) == rk;
        const uint32_t ta = sb + (ownr ? O_RAW + n0 * BS : O_STG + hw * 528) + (mi ^ 1) * 64 + (r8 & 1) * 32 + (r8 >> 2) * 16;
        const uint32_t ca = (lane & 15) * 16 + (lane >> 4) * 2 * TS8;
        const uint2* sp = prm.S->stats + (q & 1) * 2048 + n0 * 16 + (lane & 2) * 4 + g;
        uint4 x[8];
        uint2 u[8];
        uint32_t G[32];
        float h[32];
        auto load = [&](int hf) {
            mbar_wait(sb + B_X + hf * 8);
#pragma unroll
            for (int i = 4 * hf; i < 4 * hf + 4; i++) x[i] = lds128(xa + i * 2 * TS8);
        };
        auto poll = [&](int hf) {
            mbar_wait(sb + B_GO + hf * 8);
            TS(hw == 3 ? 16 + hf : 63);
            const uint2* v = u + 4 * hf;
            int it = 0;
#pragma unroll 1
            do {
#pragma unroll
                for (int i = 4 * hf; i < 4 * hf + 4; i++) u[i] = ldr64(sp + i * 256);
            } while (__any_sync(~0u, (int)(((v[0].x ^ tag) | (v[1].x ^ tag)) | ((v[2].x ^ tag) | (v[3].x ^ tag))) < 0) && ++it < 100000);
            TV(hw == 7 ? 61 + hf : 63, it);
            TS(hw == 3 ? (hf ? 25 : 18) : 63);
        };
        auto norm = [&](int i0) {
#pragma unroll
            for (int i = i0; i < i0 + 2; i++) {
                const float r = fabsf(__uint_as_float(u[i].x));
                float* v = h + 8 * (i & 3);
#pragma unroll
                for (int k = 0; k < 4; k++) {
                    const uint32_t e = bsub_lo(comp(x[i], k), u[i].y);
                    v[2 * k] = bf_lo(e) * r; v[2 * k + 1] = bf_hi(e) * r;
                }
                stsm4t(ta + i * 2 * TS8, pk_h(v[2], v[3]), pk_h(v[0], v[1]), pk_h(v[6], v[7]), pk_h(v[4], v[5]));
            }
            __syncwarp();
            st_async(pb + O_RAW + n0 * BS + ca + i0 * 2 * TS8, lds128(sb + O_STG + hw * 528 + ca + i0 * 2 * TS8), pb + B_RAW + (i0 & 4) * 2);
            if (i0 & 2) mbar_expect_e(sb + B_RAW + (i0 & 4) * 2, 1024);
        };
        auto gate = [&](int i0) {
            uint32_t* v = G + 4 * i0;
            const float* e = h + 8 * (i0 & 3);
#pragma unroll
            for (int k = 0; k < 8; k++) v[k] = pk_bf(fmaf(e[2 * k], ftanh(e[2 * k]), e[2 * k]), fmaf(e[2 * k + 1], ftanh(e[2 * k + 1]), e[2 * k + 1]));
            pin4(v[0], v[1], v[2], v[3], Z); pin4(v[4], v[5], v[6], v[7], Z);
        };
        asm volatile("barrier.cluster.wait.aligned;" ::: "memory");
        load(0); poll(0); norm(0); norm(2);
        TS(32 + hw);
        sched_fence(Z);
        gate(0); gate(2);
        TS(hw == 0 ? 20 : 63);
        load(1); poll(1); norm(4); gate(4);
        sched_fence(Z);
        norm(6);
        TS(hw == 3 ? 19 : 63);
        gate(6);
        TS(hw == 0 ? 21 : 63);
        if (RH2 < RH) asm volatile("setmaxnreg.dec.sync.aligned.u32 %0;" ::"n"(RH2));
        mbar_wait(sb + B_SEL);
        mbar_wait(sb + B_SEL + 8);
        if (hw == 0) { mbar_wait(sb + B_RAW); if (lane == 0) prm.S->epoch[b] = lds32(sb + O_SEL + 16); }
        const uint32_t tok = n0 * 16 + (lane & 2) * 4 + g, r0 = lds32(sb + O_SEL) - tok, r1 = lds32(sb + O_SEL + 8) - tok;
        const uint32_t mine = ((r0 & 255) ? 0 : 128 << (r0 >> 8)) | ((r1 & 255) ? 0 : 128 << (r1 >> 8));
        const uint32_t skip = __reduce_or_sync(~0u, mine), dir = (skip | 128 << NSTG | 256 << NSTG) & ~mine;
        const uint32_t sa = ownr ? ta - TS8 : ta;
        uint4* op = prm.out + tok * 128 + q * 2 + (lane & 1);
#pragma unroll
        for (int p = 0; p < 4; p++) {
            mbar_wait(sb + B_Y + p * 8);
#pragma unroll
            for (int i = 2 * p; i < 2 * p + 2; i++) {
                const uint4 s = ldsm4t(sa + i * 2 * TS8);
                const uint4 o = make_uint4(bfma(s.y, G[4 * i], x[i].x), bfma(s.x, G[4 * i + 1], x[i].y), bfma(s.w, G[4 * i + 2], x[i].z), bfma(s.z, G[4 * i + 3], x[i].w));
                asm volatile("{.reg .pred p; setp.ne.u32 p,%5,0; @p st.global.v4.u32 [%0],{%1,%2,%3,%4};}" ::"l"(op + i * 32768), "r"(o.x), "r"(o.y), "r"(o.z), "r"(o.w), "r"(dir & 128 << i) : "memory");
                if (i < NSTG) asm volatile("{.reg .pred p; setp.eq.u32 p,%5,0; @p st.shared.v4.u32 [%0],{%1,%2,%3,%4};}" ::"r"(xa + i * 2 * TS8), "r"(o.x), "r"(o.y), "r"(o.z), "r"(o.w), "r"(skip & 128 << i) : "memory");
            }
            if (2 * p < NSTG) {
                fence_async();
                __syncwarp();
#pragma unroll
                for (int i = 2 * p; i < 2 * p + 2; i++) tma4d_st_e(sb + O_XT + hw * 512 + i * 2 * TS8, &mo, q * 16, n0 + 16 * i + ((skip >> i) & 128));
            }
        }
        asm volatile("cp.async.bulk.commit_group; cp.async.bulk.wait_group.read 0;" ::: "memory");
        TS(40 + hw);
        TDUMP;
    } else {
        asm volatile("setmaxnreg.dec.sync.aligned.u32 %0;" ::"n"(480 - 2 * RM - 2 * RH));
        LANES;
        const int fw = w - 16;
        const CUtensorMap* m1 = &mg + rk;
        if (fw == 0) {
            bar_arrive(5, 128);
            spin(t0 + ROW1 + ((b * ROWD) >> 7));
            bulk_e(sb + O_ROWS + 16384, prm.u + (128 + b) * 1024, sb + B_ROW + 8, 16384);
            bar_sync(7, 64);
            if (b < NFFN) {
#pragma unroll 1
                for (int i = 0; i < NPF; i++) {
                    spin(t0 + W0 + ((b * WD) >> 7) + i * WD);
                    if (i == RING - 4) mbar_wait(sb + B_P1);
                    if (i < RING) tma3d_e(sb + O_RING + i * 8192, m1, i * 64, q, sb + B_FULL + i * 8);
                    else asm volatile("{.reg .pred p; elect.sync _|p,0xffffffff; @p cp.async.bulk.prefetch.tensor.3d.L2.global [%0,{0,%1,%2}];}" ::"l"(m1), "r"(i * 64), "r"(q) : "memory");
                }
            }
        } else {
            if (lane == 0) {
#pragma unroll
                for (int i = 0; i < 15; i++)
                    asm volatile("mbarrier.init.shared.b64 [%0],%1;" ::"r"(sb + B_FULL - 8 + 8 * fw + i * 24), "r"(i < 11 ? 1 : 8) : "memory");
            }
            __syncwarp();
            asm volatile("fence.mbarrier_init.release.cluster; barrier.cluster.arrive.relaxed.aligned;" ::: "memory");
            asm volatile("prefetch.tensormap [%0];" ::"l"(&md - 1 + fw));
            asm volatile("prefetch.tensormap [%0];" ::"l"(m1));
            bar_sync(5, 128);
            if (fw == 1) {
                bar_arrive(3, 288);
                bar_arrive(6, 288);
                bar_arrive(7, 64);
                mbar_expect_e(sb + B_H, 256);
                mbar_expect_e(sb + B_X, 16384);
                mbar_expect_e(sb + B_X + 8, 16384);
#pragma unroll 1
                for (int i = 0; i < 8; i++) {
                    spin(t0 + (i < 4 ? GAT0 : GAT1) + (i & 3) * GATD);
                    tma4d_e(sb + O_XT + i * 2 * TS8, &mx, q * 16, i * 16 + rk * 8, sb + B_X + (i & 4) * 2);
                }
            }
        }
        if (fw == 2) {
            spin(t0 + TGO0);
            mbar_arrive_e(sb + B_GO);
        }
        if (fw == 3) {
            uint32_t ep;
            asm volatile("ld.relaxed.gpu.global.u32 %0,[%1];" : "=r"(ep) : "l"(prm.S->epoch + b) : "memory");
            ep += 1;
            sts32(sb + O_SEL + 16, ep);
            float sw[4] = {0.f, 0.f, 0.f, 0.f};
#pragma unroll
            for (int k = 0; k < 4; k++) mma_bf(sw, ldg128(prm.wr + k * 32 + lane), 0x3f803f80u, 0x3f803f80u);
            float wsum = sw[0] + sw[2];
#pragma unroll
            for (int o = 4; o < 32; o <<= 1) wsum += __shfl_xor_sync(~0u, wsum, o);
            uint2* dst = prm.S->stats + (lane & 1) * 2048 + b * 8 + g;
            uint32_t pa = sb + O_XSEL + g * 48 + (lane & 1) * 16, ky = 0;
            const uint32_t id = (ep & 1) * 0x8000 + 2047 - (lane & 1) * 1024 - b * 8 - g;
#pragma unroll 1
            for (int hf = 0; hf < 2; hf++) {
                bar_sync(1 + 3 * hf, 288);
                float v[3];
#pragma unroll
                for (int k = 0; k < 3; k++) {
                    const uint4 t = lds128(pa + k * 384);
                    v[k] = (__uint_as_float(t.x) + __uint_as_float(t.y)) + (__uint_as_float(t.z) + __uint_as_float(t.w));
                    v[k] += __shfl_xor_sync(~0u, v[k], 1);
                }
                const float mean = v[2] * (1.f / 1024.f);
                const float var = fmaxf(fmaf(-mean, mean, v[0] * (1.f / 1024.f)), 0.f);
                const float rs = rcp(bfr(fsqrt(bfr(bfr(var) + 1e-5f))));
                const uint32_t mk = pk_bf(mean, fmaf(-bfr(mean), wsum, v[1]) * rs);
                str64(dst, __float_as_uint(0.5f * rs) | ep << 31, mk);
                if ((lane & 1) == hf) ky = ((mk ^ (((int)mk >> 31) | 0x80000000u)) & 0xffff0000u) | id;
                TS(hf ? 63 : 5);
                dst += 1024; pa += 1152;
            }
            const uint32_t k1 = __reduce_max_sync(~0u, ky), k2 = __reduce_max_sync(~0u, ky == k1 ? 0u : ky);
            str64(prm.S->keys + g * 128 + b, k1, k2);
            TS(48);
            mbar_arrive_e(sb + B_P1);
        }
        uint32_t wa[4];
#pragma unroll
        for (int i = 0; i < 4; i++) wa[i] = pin(sb + O_RING + fw * 8192 + ((mi >> 1) * 8 + r8) * 128 + (((2 * i + (mi & 1)) ^ r8) << 4));
        uint32_t xs = pin(sb + O_XSEL + fw * 128 + (r8 & 1) * 2064 + mi * 16);
        if (fw >= 2) {
            const uint2* kp = prm.S->keys + ((b & 3) * 2 + (fw & 1)) * 128 + lane * 2;
            mbar_wait(sb + B_P1);
            const uint32_t tag = lds32(sb + O_SEL + 16) << 15;
            spin(t0 + TTOP);
            uint4 k, l;
            int it = 0;
#pragma unroll 1
            do { k = ldr128(kp); l = ldr128(kp + 64); } while (__any_sync(~0u, (((k.x ^ tag) | (k.z ^ tag)) | ((l.x ^ tag) | (l.z ^ tag))) & 0x8000) && ++it < 100000);
            TV(fw == 2 ? 24 : 63, it);
            TS(fw == 2 ? 49 : 63);
            if (fw == 2) mbar_arrive_e(sb + B_GO + 8);
            uint32_t ky = __reduce_max_sync(~0u, max(max(k.x, k.z), max(l.x, l.z)));
            if (fw & 1) ky = __reduce_max_sync(~0u, max(max(k.x == ky ? k.y : k.x, k.z == ky ? k.w : k.z), max(l.x == ky ? l.y : l.x, l.z == ky ? l.w : l.z)));
            const uint32_t tok = ~ky & 2047;
            uint4 v[4];
#pragma unroll
            for (int j = 0; j < 4; j++) v[j] = ldg128(prm.u + tok * 128 + j * 32 + lane);
            uint2 rc;
#pragma unroll 1
            do rc = ldr64(prm.S->stats + (q & 1) * 2048 + tok); while ((int)(rc.x ^ tag << 16) < 0 && ++it < 100000);
            const uint32_t rsel = pk_bf(0.f, sigm(bf_hi(ky ^ (~((int)ky >> 31) | 0x80000000u))));
            const float rs = 2.f * fabsf(__uint_as_float(rc.x));
            const uint32_t r = pk_bf(rs, rs - bfr(rs));
#pragma unroll
            for (int j = 0; j < 4; j++)
                sts128(sb + O_XSEL + (fw & 1) * 2064 + j * 512 + lane * 16, norm2(v[j].x, rc.y, r), norm2(v[j].y, rc.y, r), norm2(v[j].z, rc.y, r), norm2(v[j].w, rc.y, r));
            if (lane == 0) sts64(sb + O_SEL + (fw & 1) * 8, tok, rsel);
            __syncwarp();
            mbar_arrive_e(sb + B_SEL + (fw & 1) * 8);
        }
        if (RF2 > 480 - 2 * RM - 2 * RH) asm volatile("setmaxnreg.inc.sync.aligned.u32 %0;" ::"n"(RF2));
        mbar_wait(sb + B_SEL);
        mbar_wait(sb + B_SEL + 8);
        const uint32_t ep = lds32(sb + O_SEL + 16);

        TS(fw == 1 ? 50 : 63);
        if (b < NFFN) {
            float h[4][4];
#pragma unroll
            for (int i = 0; i < 4; i++) { h[i][0] = h[i][1] = h[i][2] = h[i][3] = 0.f; }
            const bool c1 = c & 1, c2 = c & 2;
            uint4* dst = prm.S->yp + ((rk * 32 + fw * 4 + c) * 64 + q) * 8 + g;
#define PICK(k) __float_as_uint(c2 ? (c1 ? h[3][k] : h[2][k]) : (c1 ? h[1][k] : h[0][k]))
#pragma unroll 1
            for (int n = 0; n < 6; n++) {
                const int so = (n & 1) * 32768, i = fw + 4 * n;
                mbar_wait(sb + B_FULL + i * 8);
                TS(64 + i);
#pragma unroll
                for (int hf = 0; hf < 2; hf++) {
                    uint4 A[8];
                    const uint4 B = ldsm4(xs + hf * 64);
#pragma unroll
                    for (int k = 0; k < 8; k++) A[k] = ldsm4t(wa[k & 3] + so + hf * 4096 + (k >> 2) * 2048);
                    sched_fence(Z);
#pragma unroll
                    for (int k = 0; k < 8; k++) mma_bf(h[k & 3], A[k], k < 4 ? B.x : B.z, k < 4 ? B.y : B.w);
                }
                TS(96 + i);
                if (n < 4) {
                    sched_fence(Z);
                    if (n < PACE) spin(t0 + W0 + ((b * WD) >> 7) + (i + 8) * WD);
                    tma3d_e(sb + O_RING + fw * 8192 + so, n < 2 ? m1 : &md, (n < 2 ? i + 8 : q) * 64, n < 2 ? q : rk * 8 + i - 8, sb + B_FULL + i * 8 + 64);
                    xs += 512;
                    if (n < 3) continue;
                }
                const uint4 o = make_uint4(PICK(0), PICK(1), PICK(2), PICK(3));
#pragma unroll
                for (int k = 0; k < 4; k++) { h[k][0] = h[k][1] = h[k][2] = h[k][3] = 0.f; }
                if (n > 3) {
                    str128(dst, make_uint4((o.x & ~1u) | (ep & 1), o.y, o.z, o.w));
                    dst += 16 * 64 * 8;
                    continue;
                }
                sts128(sb + O_PART + fw * 512 + lane * 16, o.x, o.y, o.z, o.w);
                bar_sync(2, 128);
                TS(fw == 0 ? 51 : 63);
                if (fw < 2) {
                    const uint32_t pa = sb + O_PART + (r8 * 4 + fw * 2 + (mi >> 1)) * 16 + (mi & 1) * 8;
                    const uint2 p0 = lds64(pa), p1 = lds64(pa + 512), p2 = lds64(pa + 1024), p3 = lds64(pa + 1536);
                    uint32_t v = pk_bf((__uint_as_float(p0.x) + __uint_as_float(p1.x)) + (__uint_as_float(p2.x) + __uint_as_float(p3.x)),
                                       (__uint_as_float(p0.y) + __uint_as_float(p1.y)) + (__uint_as_float(p2.y) + __uint_as_float(p3.y)));
                    if (rk == 0) v = pk_bf(silu(bf_lo(v)), silu(bf_hi(v)));
                    asm volatile("st.async.shared::cluster.mbarrier::complete_tx::bytes.b32 [%0],%1,[%2];" ::"r"(pb + O_HX + fw * 128 + lane * 4), "r"(v), "r"(pb + B_H) : "memory");
                    mbar_wait(sb + B_H);
                    v = bmul(v, lds32(sb + O_HX + fw * 128 + lane * 4));
                    sts16(sb + O_HT + fw * 64 + lane * 2, v); sts16(sb + O_HT + 144 + fw * 64 + lane * 2, v >> 16);
                }
                xs = sb + O_HT + (r8 & 1) * 144 + mi * 16;
                bar_sync(2, 128);
                TS(fw == 0 ? 52 : 63);
            }
            TS(fw == 0 ? 63 : 52 + fw);
        }
        const uint2 sel = lds64(sb + O_SEL + (lane & 1) * 8);
        const bool own = ((sel.x >> 7) & 1) == rk;
        if (!NOFIX && __any_sync(~0u, own)) {
            uint32_t xv;
            if (fw == 0) asm volatile("ld.global.nc.u16 %0,[%1];" : "=r"(xv) : "l"((const uint16_t*)prm.u + sel.x * 1024 + q * 16 + (lane >> 1)) : "memory");
            spin(t0 + TFIX);
            bar_sync(2, 128);
            const uint4* yp = prm.S->yp + q * 512 + fw * 32 + lane;
            float y[4];
            int it = 0;
            uint32_t bad;
#pragma unroll 1
            do {
                uint4 v[4];
#pragma unroll
                for (int j = 0; j < 3; j++) v[j] = ldr128(yp + j * 128);
                v[3] = make_uint4(ep & 1, 0, 0, 0);
                if (fw < 2) v[3] = ldr128(yp + 384);
                y[0] = y[1] = y[2] = y[3] = 0.f;
                bad = 0;
#pragma unroll
                for (int j = 0; j < 4; j++) {
                    y[0] += __uint_as_float(v[j].x); y[1] += __uint_as_float(v[j].y); y[2] += __uint_as_float(v[j].z); y[3] += __uint_as_float(v[j].w);
                    bad |= v[j].x ^ ep;
                }
            } while (__any_sync(~0u, bad & 1) && ++it < 100000);
            TV(fw == 0 ? 57 : 63, it);
            sts128(sb + O_PART + fw * 512 + lane * 16, __float_as_uint(y[0]), __float_as_uint(y[1]), __float_as_uint(y[2]), __float_as_uint(y[3]));
            bar_sync(2, 128);
            if (fw == 0) {
                const uint32_t pa = sb + O_PART + (lane & 14) * 8 + (lane >> 4) * 8 + (lane & 1) * 4;
                float t[2] = {0.f, 0.f};
#pragma unroll
                for (int j = 0; j < 16; j++) t[j & 1] += __uint_as_float(lds32(pa + j * 128));
                const float xn = bf_lo(lds16(sb + O_XSEL + (lane & 1) * 2064 + q * 32 + (lane >> 1) * 2));
                const float gt = bfr(silu(bfr(xn + bfr(bfr(t[0] + t[1]) * __uint_as_float(sel.y)))));
                TS(56);
                const uint32_t n = sel.x >> 4;
                const uint32_t sa = sb + ((lane >> 4) == rk ? O_RAW - TS8 + n * BS : O_STG + (n >> 4) * 2 * TS8 + (n & 7) * 528) + (lane & 14) * 16;
                mbar_wait(sb + B_Y + __reduce_max_sync(~0u, own ? n >> 5 : 0) * 8);
                if (own) ((uint16_t*)prm.out)[sel.x * 1024 + q * 16 + (lane >> 1)] = pk_bf(fmaf(bf_lo(lds16(sa + (sel.x & 15) * 2)), gt, bf_lo(xv)), 0.f);
                TS(7);
            }
        }
        TDUMP;
    }
}

typedef CUresult (*EncFn)(CUtensorMap*, CUtensorMapDataType, cuuint32_t, void*, const cuuint64_t*, const cuuint64_t*,
                          const cuuint32_t*, const cuuint32_t*, CUtensorMapInterleave, CUtensorMapSwizzle,
                          CUtensorMapL2promotion, CUtensorMapFloatOOBfill);

void make_map(EncFn f, CUtensorMap* m, const void* p, int rank, const cuuint64_t* gd, const cuuint64_t* gs,
              const cuuint32_t* bd, CUtensorMapSwizzle sw) {
    const cuuint32_t es[4] = {1, 1, 1, 1};
    f(m, CU_TENSOR_MAP_DATA_TYPE_BFLOAT16, rank, const_cast<void*>(p), gd, gs, bd, es, CU_TENSOR_MAP_INTERLEAVE_NONE, sw,
      CU_TENSOR_MAP_L2_PROMOTION_NONE, CU_TENSOR_MAP_FLOAT_OOB_FILL_NONE);
}

}

extern "C" void kernel_launch(void* const* d_in, const int* in_sizes, int n_in, void* d_out, int out_size) {
    (void)in_sizes; (void)n_in; (void)out_size;
    void* fp = nullptr;
    cudaDriverEntryPointQueryResult qr;
    cudaGetDriverEntryPoint("cuTensorMapEncodeTiled", &fp, cudaEnableDefault, &qr);
    EncFn enc = (EncFn)fp;
    Maps maps;
    CUtensorMap &mg = maps.m[0], &mu = maps.m[1], &md = maps.m[2], &mx = maps.m[3], &mo = maps.m[4];
    {
        const cuuint64_t gd[3] = {64, 1024, 56}, gs[2] = {7168, 128};
        const cuuint32_t bd[3] = {64, 64, 1};
        make_map(enc, &mg, d_in[9], 3, gd, gs, bd, CU_TENSOR_MAP_SWIZZLE_128B);
        make_map(enc, &mu, d_in[10], 3, gd, gs, bd, CU_TENSOR_MAP_SWIZZLE_128B);
    }
    {
        const cuuint64_t gd[3] = {64, 3584, 16}, gs[2] = {2048, 128};
        const cuuint32_t bd[3] = {64, 64, 1};
        make_map(enc, &md, d_in[11], 3, gd, gs, bd, CU_TENSOR_MAP_SWIZZLE_128B);
    }
    {
        const cuuint64_t gd[4] = {1024, 2, 8, 128}, gs[3] = {16384, 2048, 32768};
        const cuuint32_t bd[4] = {16, 2, 8, 8}, bo[4] = {16, 2, 8, 1};
        make_map(enc, &mo, d_out, 4, gd, gs, bo, CU_TENSOR_MAP_SWIZZLE_NONE);
        make_map(enc, &mx, d_in[0], 4, gd, gs, bd, CU_TENSOR_MAP_SWIZZLE_NONE);
    }
    Params p;
    p.u = (const uint4*)d_in[0]; p.logA = (const uint2*)d_in[1]; p.Aim = (const uint2*)d_in[2];
    p.Cre = (const uint2*)d_in[3]; p.Cim = (const uint2*)d_in[4];
    p.logdt = (const uint16_t*)d_in[5]; p.Dsk = (const uint16_t*)d_in[6]; p.wr = (const uint4*)d_in[8];
    p.out = (uint4*)d_out;
    void* sp = nullptr;
    cudaGetSymbolAddress(&sp, g_scratch);
    p.S = (Scratch*)sp; p.zero = 0;
    cudaFuncSetAttribute(fused_kernel, cudaFuncAttributeMaxDynamicSharedMemorySize, SMEM_BYTES + 512);
    fused_kernel<<<128, 640, SMEM_BYTES + 512, cudaStreamPerThread>>>(p, maps);
}
```

```cpp
#include <cuda_runtime.h>
#include <cuda_bf16.h>
#include <cuda_fp16.h>
#include <cuda.h>
#include <stdint.h>

#define RM 112
#define RH 88
#define NSTG 6
#define ORD 0
#define FSB 1
#define RH2 RH
#define RF2 (480 - 2 * RM - 2 * RH2)
#define KV 1
#define FUNROLL 1
#define NOFIX 0
#define NFFN 112
namespace {

constexpr int RING = 8, FUN = FUNROLL;
constexpr uint32_t BS = 272, TS8 = 8 * BS;
constexpr uint32_t O_RING = 0;
constexpr uint32_t O_XT   = RING * 8192;
constexpr uint32_t O_STG  = O_XT + 64;
constexpr uint32_t O_RAW  = O_XT + 17 * TS8;
constexpr uint32_t O_PRIV = O_RAW + 16 * TS8;
constexpr uint32_t PRIV   = 7760;
constexpr uint32_t P_TAB  = 4224;
constexpr uint32_t O_XSEL = O_PRIV + 8 * PRIV;
constexpr uint32_t O_MISC = O_XSEL + 4160;
constexpr uint32_t O_ROWS = (RING - 4) * 8192;
constexpr uint32_t O_PART = O_MISC;
constexpr uint32_t O_HX   = O_PART + 2048;
constexpr uint32_t O_HT   = O_HX + 256;
constexpr uint32_t O_SEL  = O_HT + 288;
constexpr uint32_t O_BAR  = O_SEL + 32;
constexpr uint32_t B_ROW = O_BAR, B_FULL = B_ROW + 16, B_H = B_FULL + 8 * 24, B_SEL = B_H + 8, B_P1 = B_SEL + 16,
                   B_X = B_P1 + 8, B_GO = B_X + 16, B_Y = B_GO + 24, B_RAW = B_Y + 64;
constexpr uint32_t SMEM_BYTES = B_Y + 96;
static_assert(B_Y - B_FULL == 11 * 24 && O_RAW % 128 == 0 && O_STG % 128 == 64, "layout");
static_assert(SMEM_BYTES <= 232448, "smem");
constexpr int T1 = 18, T4 = 561, T2 = 596, T3 = 756;

#define SCHED(X) X(0, ROW0, 300) X(1, ROW1, 1000) X(2, ROWD, 0) X(3, GAT0, 900) X(4, GAT1, 4400) X(5, GATD, 60) X(6, TGO0, 2700) \
    X(7, TTOP, 3800) X(8, W0, 1700) X(9, WD, 280) X(10, NPF, 10) X(11, PACE, 4) X(13, TFIX, 10300)
#define X(i, n, v) constexpr int n = v;

struct Scratch {
    uint2 stats[2 * 2048];
    uint2 keys[8 * 128];
    uint4 yp[64 * 64 * 8];
    unsigned epoch[128];
    int ts[128 * 128];
};
__device__ Scratch g_scratch;

struct Maps { CUtensorMap m[5]; };
struct Params {
    const uint4* u; const uint2* logA; const uint2* Aim; const uint2* Cre; const uint2* Cim;
    const uint16_t* logdt; const uint16_t* Dsk; const uint4* wr;
    uint4* out; Scratch* S; uint32_t zero;
};

#define DI __device__ __forceinline__
DI int lane_id() { int l; asm volatile("mov.u32 %0,%%laneid;" : "=r"(l)); __builtin_assume(l >= 0 && l < 32); return l; }
DI uint32_t pin(uint32_t v) { return __shfl_sync(~0u, v, lane_id()); }
DI int now_ns() { int c; asm volatile("mov.u32 %0,%%globaltimer_lo;" : "=r"(c)::"memory"); return c; }
DI void spin(int t) {
    asm volatile("{.reg .pred p; .reg .s32 c; L: mov.u32 c,%%globaltimer_lo; sub.s32 c,c,%0; setp.lt.s32 p,c,0; @p nanosleep.u32 32; @p bra.uni L;}" ::"r"(t) : "memory");
}
DI void mbar_arrive_e(uint32_t b) { asm volatile("{.reg .pred p; elect.sync _|p,0xffffffff; @p mbarrier.arrive.shared.b64 _,[%0];}" ::"r"(b) : "memory"); }
DI void mbar_expect_e(uint32_t b, int tx) { asm volatile("{.reg .pred p; elect.sync _|p,0xffffffff; @p mbarrier.arrive.expect_tx.shared.b64 _,[%0],%1;}" ::"r"(b), "r"(tx) : "memory"); }
DI void mbar_wait(uint32_t b) {
    asm volatile("{.reg .pred p; W: mbarrier.try_wait.parity.shared.b64 p,[%0],0; @!p bra.uni W; }" ::"r"(b) : "memory");
}
DI void bulk_e(uint32_t dst, const void* src, uint32_t bar, int bytes) {
    asm volatile("{.reg .pred p; elect.sync _|p,0xffffffff; @p cp.async.bulk.shared::cluster.global.mbarrier::complete_tx::bytes [%0],[%1],%3,[%2];}" ::"r"(dst), "l"(src), "r"(bar), "r"(bytes) : "memory");
}
DI void tma3d_e(uint32_t dst, const CUtensorMap* m, int c1, int c2, uint32_t bar) {
    asm volatile("{.reg .pred p; elect.sync _|p,0xffffffff; @p mbarrier.arrive.expect_tx.shared.b64 _,[%2],8192;\n"
                 "@p cp.async.bulk.tensor.3d.shared::cluster.global.mbarrier::complete_tx::bytes [%0],[%1,{0,%3,%4}],[%2];}" ::"r"(dst), "l"(m), "r"(bar), "r"(c1), "r"(c2) : "memory");
}
DI void tma4d_e(uint32_t dst, const CUtensorMap* m, int c0, int c3, uint32_t bar) {
    asm volatile("{.reg .pred p; elect.sync _|p,0xffffffff;\n"
                 "@p cp.async.bulk.tensor.4d.shared::cluster.global.mbarrier::complete_tx::bytes [%0],[%1,{%3,0,0,%4}],[%2];}" ::"r"(dst), "l"(m), "r"(bar), "r"(c0), "r"(c3) : "memory");
}
DI void tma4d_st_e(uint32_t src, const CUtensorMap* m, int c0, int c3) {
    asm volatile("{.reg .pred p; elect.sync _|p,0xffffffff; @p cp.async.bulk.tensor.4d.global.shared::cta.bulk_group [%1,{%2,0,0,%3}],[%0];}" ::"r"(src), "l"(m), "r"(c0), "r"(c3) : "memory");
}
DI void st_async(uint32_t dst, const uint4& v, uint32_t bar) {
    asm volatile("st.async.shared::cluster.mbarrier::complete_tx::bytes.v4.b32 [%0],{%1,%2,%3,%4},[%5];" ::"r"(dst), "r"(v.x), "r"(v.y), "r"(v.z), "r"(v.w), "r"(bar) : "memory");
}
DI void fence_async() { asm volatile("fence.proxy.async.shared::cta;" ::: "memory"); }
DI void bar_sync(int id, int n) { asm volatile("bar.sync %0,%1;" ::"r"(id), "r"(n) : "memory"); }
DI void bar_arrive(int id, int n) { asm volatile("bar.arrive %0,%1;" ::"r"(id), "r"(n) : "memory"); }
DI uint4 ldg128(const void* p) { uint4 v; asm volatile("ld.global.nc.v4.u32 {%0,%1,%2,%3},[%4];" : "=r"(v.x), "=r"(v.y), "=r"(v.z), "=r"(v.w) : "l"(p) : "memory"); return v; }
DI uint2 ldg64(const void* p) { uint2 v; asm volatile("ld.global.nc.v2.u32 {%0,%1},[%2];" : "=r"(v.x), "=r"(v.y) : "l"(p) : "memory"); return v; }
DI uint4 ldr128(const void* p) {
    uint4 v;
    asm volatile("{.reg .b128 t; .reg .b64 a,b; ld.relaxed.gpu.global.b128 t,[%4]; mov.b128 {a,b},t; mov.b64 {%0,%1},a; mov.b64 {%2,%3},b;}"
                 : "=r"(v.x), "=r"(v.y), "=r"(v.z), "=r"(v.w) : "l"(p) : "memory");
    return v;
}
DI uint2 ldr64(const void* p) { uint2 v; asm volatile("{.reg .b64 t; ld.relaxed.gpu.global.b64 t,[%2]; mov.b64 {%0,%1},t;}" : "=r"(v.x), "=r"(v.y) : "l"(p) : "memory"); return v; }
DI void str64(void* p, uint32_t x, uint32_t y) { asm volatile("{.reg .b64 t; mov.b64 t,{%1,%2}; st.relaxed.gpu.global.b64 [%0],t;}" ::"l"(p), "r"(x), "r"(y) : "memory"); }
DI void str128(void* p, uint4 v) {
    asm volatile("{.reg .b128 t; .reg .b64 a,b; mov.b64 a,{%1,%2}; mov.b64 b,{%3,%4}; mov.b128 t,{a,b}; st.relaxed.gpu.global.b128 [%0],t;}" ::"l"(p), "r"(v.x), "r"(v.y), "r"(v.z), "r"(v.w) : "memory");
}
DI uint32_t lds32(uint32_t a) { uint32_t v; asm volatile("ld.shared.u32 %0,[%1];" : "=r"(v) : "r"(a) : "memory"); return v; }
DI uint32_t lds16(uint32_t a) { uint32_t v; asm volatile("ld.shared.u16 %0,[%1];" : "=r"(v) : "r"(a) : "memory"); return v; }
DI uint2 lds64(uint32_t a) { uint2 v; asm volatile("ld.shared.v2.u32 {%0,%1},[%2];" : "=r"(v.x), "=r"(v.y) : "r"(a) : "memory"); return v; }
DI uint4 lds128(uint32_t a) { uint4 v; asm volatile("ld.shared.v4.u32 {%0,%1,%2,%3},[%4];" : "=r"(v.x), "=r"(v.y), "=r"(v.z), "=r"(v.w) : "r"(a) : "memory"); return v; }
DI void sts16(uint32_t a, uint32_t v) { asm volatile("st.shared.u16 [%0],%1;" ::"r"(a), "r"(v) : "memory"); }
DI void sts32(uint32_t a, uint32_t v) { asm volatile("st.shared.u32 [%0],%1;" ::"r"(a), "r"(v) : "memory"); }
DI void sts64(uint32_t a, uint32_t x, uint32_t y) { asm volatile("st.shared.v2.u32 [%0],{%1,%2};" ::"r"(a), "r"(x), "r"(y) : "memory"); }
DI void sts128(uint32_t a, uint32_t x, uint32_t y, uint32_t z, uint32_t w) { asm volatile("st.shared.v4.u32 [%0],{%1,%2,%3,%4};" ::"r"(a), "r"(x), "r"(y), "r"(z), "r"(w) : "memory"); }
DI uint4 ldsm4(uint32_t a) { uint4 v; asm volatile("ldmatrix.sync.aligned.m8n8.x4.shared.b16 {%0,%1,%2,%3},[%4];" : "=r"(v.x), "=r"(v.y), "=r"(v.z), "=r"(v.w) : "r"(a) : "memory"); return v; }
DI uint4 ldsm4t(uint32_t a) { uint4 v; asm volatile("ldmatrix.sync.aligned.m8n8.x4.trans.shared.b16 {%0,%1,%2,%3},[%4];" : "=r"(v.x), "=r"(v.y), "=r"(v.z), "=r"(v.w) : "r"(a) : "memory"); return v; }
DI void stsm4(uint32_t a, uint32_t x, uint32_t y, uint32_t z, uint32_t w) { asm volatile("stmatrix.sync.aligned.m8n8.x4.shared.b16 [%0],{%1,%2,%3,%4};" ::"r"(a), "r"(x), "r"(y), "r"(z), "r"(w) : "memory"); }
DI void stsm4t(uint32_t a, uint32_t x, uint32_t y, uint32_t z, uint32_t w) { asm volatile("stmatrix.sync.aligned.m8n8.x4.trans.shared.b16 [%0],{%1,%2,%3,%4};" ::"r"(a), "r"(x), "r"(y), "r"(z), "r"(w) : "memory"); }
DI void mma_bf(float (&d)[4], uint32_t a0, uint32_t a1, uint32_t a2, uint32_t a3, uint32_t b0, uint32_t b1) {
    asm("mma.sync.aligned.m16n8k16.row.col.f32.bf16.bf16.f32 {%0,%1,%2,%3},{%4,%5,%6,%7},{%8,%9},{%0,%1,%2,%3};"
        : "+f"(d[0]), "+f"(d[1]), "+f"(d[2]), "+f"(d[3]) : "r"(a0), "r"(a1), "r"(a2), "r"(a3), "r"(b0), "r"(b1));
}
DI void mma_bf(float (&d)[4], const uint4& a, uint32_t b0, uint32_t b1) { mma_bf(d, a.x, a.y, a.z, a.w, b0, b1); }
typedef uint32_t h4[2];
DI void mma_h(h4& d, const uint4& a, uint32_t b0, uint32_t b1) {
    asm("mma.sync.aligned.m16n8k16.row.col.f16.f16.f16.f16 {%0,%1},{%2,%3,%4,%5},{%6,%7},{%0,%1};"
        : "+r"(d[0]), "+r"(d[1]) : "r"(a.x), "r"(a.y), "r"(a.z), "r"(a.w), "r"(b0), "r"(b1));
}
DI void mma_k8(h4& d, uint32_t a0, uint32_t a1, uint32_t b0) {
    asm("mma.sync.aligned.m16n8k8.row.col.f16.f16.f16.f16 {%0,%1},{%2,%3},{%4},{%0,%1};" : "+r"(d[0]), "+r"(d[1]) : "r"(a0), "r"(a1), "r"(b0));
}
DI void mma_cvt(float (&d)[4], const h4& a, uint32_t b) {
    asm("mma.sync.aligned.m16n8k8.row.col.f32.f16.f16.f32 {%0,%1,%2,%3},{%4,%5},{%6},{%7,%7,%7,%7};"
        : "=f"(d[0]), "=f"(d[1]), "=f"(d[2]), "=f"(d[3]) : "r"(a[0]), "r"(a[1]), "r"(b), "f"(0.f));
}
DI uint32_t pk_bf(float lo, float hi) { uint32_t r; asm("cvt.rn.bf16x2.f32 %0,%1,%2;" : "=r"(r) : "f"(hi), "f"(lo)); return r; }
DI uint32_t pk_h(float lo, float hi) { uint32_t r; asm("cvt.rn.f16x2.f32 %0,%1,%2;" : "=r"(r) : "f"(hi), "f"(lo)); return r; }
DI float bf_lo(uint32_t v) { return __uint_as_float(v << 16); }
DI float bf_hi(uint32_t v) { return __uint_as_float(v & 0xffff0000u); }
DI float bfr(float x) { return bf_lo(pk_bf(x, 0.f)); }
DI uint32_t hadd(uint32_t a, uint32_t b) { uint32_t r; asm("add.rn.f16x2 %0,%1,%2;" : "=r"(r) : "r"(a), "r"(b)); return r; }
DI uint32_t hsub(uint32_t a, uint32_t b) { uint32_t r; asm volatile("sub.rn.f16x2 %0,%1,%2;" : "=r"(r) : "r"(a), "r"(b)); return r; }
DI uint32_t hscl(uint32_t a) { uint32_t r; asm("mul.rn.f16x2 %0,%1,%2;" : "=r"(r) : "r"(a), "r"(0x01000100)); return r; }
DI uint32_t bsub_lo(uint32_t x, uint32_t m) { uint32_t r; asm("{.reg .b16 l,h; .reg .b32 t; mov.b32 {l,h},%2; mov.b32 t,{l,l}; sub.rn.bf16x2 %0,%1,t;}" : "=r"(r) : "r"(x), "r"(m)); return r; }
DI uint32_t bmul(uint32_t a, uint32_t b) { uint32_t r; asm("mul.rn.bf16x2 %0,%1,%2;" : "=r"(r) : "r"(a), "r"(b)); return r; }
DI uint32_t bfma(uint32_t a, uint32_t b, uint32_t c) { uint32_t r; asm("fma.rn.bf16x2 %0,%1,%2,%3;" : "=r"(r) : "r"(a), "r"(b), "r"(c)); return r; }
DI uint32_t norm2(uint32_t x, uint32_t m, uint32_t r) {
    uint32_t o;
    asm("{.reg .b16 l,h; .reg .b32 t,e; mov.b32 {l,h},%2; mov.b32 t,{h,h}; mul.rn.bf16x2 e,%1,t; mov.b32 t,{l,l}; fma.rn.bf16x2 %0,%1,t,e;}" : "=r"(o) : "r"(bsub_lo(x, m)), "r"(r));
    return o;
}
DI float ex2(float x) { float r; asm("ex2.approx.ftz.f32 %0,%1;" : "=f"(r) : "f"(x)); return r; }
DI float rcp(float x) { float r; asm("rcp.approx.ftz.f32 %0,%1;" : "=f"(r) : "f"(x)); return r; }
DI float ftanh(float x) { float r; asm("tanh.approx.f32 %0,%1;" : "=f"(r) : "f"(x)); return r; }
DI float fsqrt(float x) { float r; asm("sqrt.approx.ftz.f32 %0,%1;" : "=f"(r) : "f"(x)); return r; }
constexpr float LOG2E = 1.4426950408889634f;
DI float sigm(float x) { return rcp(1.f + ex2(-LOG2E * x)); }
DI float silu(float x) { return x * sigm(x); }
struct cf { float r, i; };
DI cf cmul(cf a, cf b) { return {fmaf(a.r, b.r, -a.i * b.i), fmaf(a.r, b.i, a.i * b.r)}; }
DI float mul2(float a, float b) { float r; asm("{.reg .f32 t; mul.f32 t,%1,%2; mul.f32 %0,t,0f40000000;}" : "=f"(r) : "f"(a), "f"(b)); return r; }
DI cf csq(cf a) { return {fmaf(a.r, a.r, -a.i * a.i), mul2(a.r, a.i)}; }
DI cf csqc(cf a) { return {fmaf(a.r, a.r, -a.i * a.i), mul2(a.r, -a.i)}; }
DI cf cexp(float a2, float be, float p) { float m = ex2(a2 * p); float t = be * p; return {m * __cosf(t), m * __sinf(t)}; }

struct ch2 { uint32_t r, i; };
template <int V>
DI ch2 hmul(ch2 a, uint32_t fr, uint32_t fi) {
    ch2 o;
    if (V) asm("{.reg .b32 t,u; mul.rn.f16x2 t,%3,%5; neg.f16x2 t,t; mul.rn.f16x2 u,%2,%5; fma.rn.f16x2 %0,%2,%4,t; fma.rn.f16x2 %1,%3,%4,u;}"
               : "=&r"(o.r), "=r"(o.i) : "r"(a.r), "r"(a.i), "r"(fr), "r"(fi));
    else asm("{.reg .b32 t,u,n; mul.rn.f16x2 t,%2,%4; mul.rn.f16x2 u,%3,%4; neg.f16x2 n,%3; fma.rn.f16x2 %0,n,%5,t; fma.rn.f16x2 %1,%2,%5,u;}"
             : "=&r"(o.r), "=r"(o.i) : "r"(a.r), "r"(a.i), "r"(fr), "r"(fi));
    return o;
}
DI ch2 hmul(ch2 a, uint32_t f) {
    ch2 o;
    asm("{.reg .b32 t,u,x,y; .reg .b16 l,h; mov.b32 {l,h},%4; mov.b32 x,{l,l}; mov.b32 y,{h,h};\n"
        "mul.rn.f16x2 t,%3,y; neg.f16x2 t,t; fma.rn.f16x2 %0,%2,x,t; mul.rn.f16x2 u,%3,x; fma.rn.f16x2 %1,%2,y,u;}"
        : "=&r"(o.r), "=r"(o.i) : "r"(a.r), "r"(a.i), "r"(f));
    return o;
}
DI uint32_t pk_h(cf f) { return pk_h(f.r, f.i); }
DI void sts_ch2(uint32_t a, ch2 x, ch2 y, ch2 z, ch2 w) { sts128(a, x.r, y.r, z.r, w.r); sts128(a + 512, x.i, y.i, z.i, w.i); }

#define TDUMP
#define TS(i)
#define TV(i, v)
#define T2S(i)

DI uint4 toep(uint32_t a, uint32_t Z) {
    uint4 r; r.x = lds32(a); r.y = lds32(a + 32); r.z = lds32(a - 32); r.w = r.x ^ Z;
    return r;
}
DI void sched_fence(uint32_t Z) { if (FSB == 2) { asm volatile("griddepcontrol.launch_dependents;" ::: "memory"); return; } asm volatile("{.reg .pred p; setp.ne.u32 p,%0,0; @p griddepcontrol.launch_dependents;}" ::"r"(Z) : "memory"); }
DI uint32_t copy(uint32_t v, uint32_t Z) { uint32_t r; asm volatile("xor.b32 %0,%1,%2;" : "=r"(r) : "r"(v), "r"(Z)); return r; }
DI void pin4(uint32_t& a, uint32_t& b, uint32_t& c, uint32_t& d, uint32_t Z) {
    asm volatile("{.reg .pred p; setp.ne.u32 p,%4,0; @p ld.shared.v4.u32 {%0,%1,%2,%3},[%4];}" : "+r"(a), "+r"(b), "+r"(c), "+r"(d) : "r"(Z) : "memory");
}

#define BFRAG(B, s) ((s) & 1) ? B[(s) >> 1].z : B[(s) >> 1].x, ((s) & 1) ? B[(s) >> 1].w : B[(s) >> 1].y
DI uint32_t comp(const uint4& v, int k) { return k == 0 ? v.x : k == 1 ? v.y : k == 2 ? v.z : v.w; }
template <bool FIRST>
DI void conv_half(h4 (&acc)[16], uint32_t aA, uint32_t aB, uint32_t aE, uint32_t bar, uint32_t Z) {
    constexpr int O = FIRST ? 0 : 8, NT = FIRST ? 5 : 4;
    uint4 A[4], S[2], B[4] = {};
    h4 P[4], m1[5] = {};
#pragma unroll
    for (int i = 0; i < 4; i++) A[i] = toep(aA + 7 * 64 + i * 512, Z);
    S[0].z = hsub(A[0].y, A[1].y); S[1].z = hsub(A[2].y, A[3].y);
    if (!FIRST || ORD)
#pragma unroll
        for (int k = 0; k < 2 * NT; k++) acc[O + (k | 1)][k & 1] = hsub(acc[O + (k | 1)][k & 1], acc[O + (k & ~1)][k & 1]);
    auto refill = [&](int k) { A[k].y = copy(A[k].z, Z); A[k].x = lds32(aA + 6 * 64 + k * 512); A[k].z = lds32(aA + 6 * 64 + k * 512 - 32); };
    auto diff = [&](int k) {
        A[2 * k].w = copy(A[2 * k].x, Z); A[2 * k + 1].w = copy(A[2 * k + 1].x, Z);
        S[k].y = copy(S[k].z, Z); S[k].z = hsub(A[2 * k].z, A[2 * k + 1].z); S[k].x = hsub(A[2 * k].x, A[2 * k + 1].w); S[k].w = hsub(A[2 * k].w, A[2 * k + 1].x);
    };
    auto pre = [&](int s) { P[s][0] = hsub(B[s].z, B[s].x); P[s][1] = hsub(B[s].w, B[s].y); };
    auto head = [&]() {
#pragma unroll
        for (int s = 0; s < 4; s++) {
            if (s) pre(s - 1);
            if (s == 2) diff(1);
            mma_h(acc[O + 2 * s], A[0], B[s].x, B[s].y); mma_h(m1[s], A[1], B[s].z, B[s].w);
            sched_fence(Z);
        }
    };
    auto rest = [&](bool ld) {
        pre(3);
        if (ld) { refill(0); refill(1); }
#pragma unroll
        for (int s = 0; s + 1 < NT; s++) {
            mma_h(acc[O + 2 * s + 2], A[2], B[s].x, B[s].y); mma_h(m1[s + 1], A[3], B[s].z, B[s].w);
            if (ld) { sched_fence(Z); B[s] = ldsm4(aB - 6 * BS + s * 2 * TS8); }
        }
        if (ld && NT == 4) B[3] = ldsm4(aB - 6 * BS + 6 * TS8);
        if (ld) { refill(2); refill(3); }
#pragma unroll
        for (int s = 0; s < 4; s++) mma_h(acc[O + 2 * ((s + !FIRST) & 3) + 1], S[0], P[(s + !FIRST) & 3][0], P[(s + !FIRST) & 3][1]);
        if (ld) { sched_fence(Z); diff(0); }
        if (FIRST) mma_h(acc[9], S[1], P[3][0], P[3][1]);
#pragma unroll
        for (int s = 0; s < 3; s++) mma_h(acc[O + 2 * s + 3], S[1], P[s][0], P[s][1]);
        if (ld) sched_fence(Z);
    };
    diff(0);
    if (FIRST && !ORD) { pin4(A[0].x, A[0].y, A[0].z, A[0].w, Z); pin4(A[1].x, A[1].y, A[1].z, A[1].w, Z); pin4(S[0].x, S[0].y, S[0].z, S[0].w, Z); }
    if (!ORD) mbar_wait(bar);
#pragma unroll
    for (int i = 0; i < 4; i++) B[i] = ldsm4(aB - 7 * BS + i * 2 * TS8);
    head();
#pragma unroll FUN
    for (int n = 0; n < 7; n++) {
        rest(true);
        head();
        aA -= 64; aB += BS;
    }
    if (ORD && FIRST) mbar_wait(bar + 8);
    const uint4 A32 = toep(aA + 448 + 2048, Z);
    uint4 A64, E[2];
    E[0] = ldsm4(aE);
    if (FIRST) { A64 = toep(aA + 448 + (T4 - T1) * 4, Z); E[1] = ldsm4(aE + 4 * TS8); }
    const uint4 Y = make_uint4(A32.y ^ Z, A32.y & Z, FIRST ? A64.y ^ Z : 0, FIRST ? A64.y & Z : 0);
    rest(false);
#pragma unroll
    for (int k = 0; k < 2 * NT; k++) acc[O + (k | 1)][k & 1] = hadd(hadd(acc[O + (k & ~1)][k & 1], m1[k >> 1][k & 1]), acc[O + (k | 1)][k & 1]);
#pragma unroll
    for (int k = 0; k < (FIRST ? 10 : 6); k++) {
        if (k < 8 || ORD) acc[O + 2 + (k & ~1)][k & 1] = hadd(acc[O + 2 + (k & ~1)][k & 1], m1[k >> 1][k & 1]);
        else acc[10][k & 1] = m1[4][k & 1];
    }
    if (FIRST) {
#pragma unroll
        for (int s = 7; s >= 0; s--) mma_h(acc[s + 8], A64, BFRAG(B, s));
#pragma unroll
        for (int s = 7; s >= 0; s--) mma_k8(acc[s + 8], Y.z, Y.w, comp(E[s >> 2], s & 3));
    }
#pragma unroll
    for (int s = 0; s < (FIRST ? 8 : 4); s++) mma_h(acc[O + s + 4], A32, BFRAG(B, s));
#pragma unroll
    for (int s = 0; s < (FIRST ? 8 : 4); s++) mma_k8(acc[O + s + 4], Y.x, Y.y, comp(E[s >> 2], s & 3));
}

__global__ void __cluster_dims__(2, 1, 1) __launch_bounds__(640, 1)
fused_kernel(const __grid_constant__ Params prm, const __grid_constant__ Maps maps) {
    const CUtensorMap &mg = maps.m[0], &md = maps.m[2], &mx = maps.m[3], &mo = maps.m[4];
    extern __shared__ __align__(1024) unsigned char smem_raw[];
    SCHED(X)
    const uint32_t tid = threadIdx.x;
    uint2 vA, vI, vR, vC;
    uint32_t ldt, Dsk;
    if (tid < 256) {
        const int e = blockIdx.x * 256 + tid;
        vA = ldg64(prm.logA + e); vI = ldg64(prm.Aim + e); vR = ldg64(prm.Cre + e); vC = ldg64(prm.Cim + e);
        ldt = prm.logdt[e >> 5]; Dsk = prm.Dsk[e >> 5];
    }
    const int t0 = __shfl_sync(~0u, now_ns() + (threadIdx.x >> 10), 0);
    const uint32_t sb = (uint32_t)__cvta_generic_to_shared(smem_raw);
    const int b = blockIdx.x, rk = b & 1, q = b >> 1;
    const int w = __shfl_sync(~0u, tid >> 5, 0);
#define LANES const int lane = lane_id(), g = lane >> 2, c = lane & 3, mi = lane >> 3, r8 = lane & 7; (void)g; (void)c; (void)mi; (void)r8
    uint32_t pb;
    asm("mapa.shared::cluster.u32 %0,%1,%2;" : "=r"(pb) : "r"(sb), "r"(rk ^ 1));
    if (w < 17) asm volatile("barrier.cluster.arrive.relaxed.aligned;" ::: "memory");
    const uint32_t Z = prm.zero;
    if (w == 16) {
        asm volatile("{.reg .pred p; elect.sync _|p,0xffffffff; @p mbarrier.init.shared.b64 [%0],1; @p mbarrier.init.shared.b64 [%0+8],1; fence.mbarrier_init.release.cluster;\n"
                     "@p mbarrier.arrive.expect_tx.shared.b64 _,[%0],16384; @p mbarrier.arrive.expect_tx.shared.b64 _,[%0+8],16384;}" ::"r"(sb + B_ROW) : "memory");
        if (ROW0) spin(t0 + ROW0);
        bulk_e(sb + O_ROWS, prm.u + b * 1024, sb + B_ROW, 16384);
        TS(6);
    }

    if (w < 8) {
        LANES;
        const uint32_t pv = sb + O_PRIV + w * PRIV, tb = pv + P_TAB, rw = sb + O_RAW + w * 32;
        const uint32_t st = pv + lane * 16;
        uint32_t cyP = pv + 528 + c * 1056 + mi * 4;
        sts64(rw - TS8 + g * BS + c * 8, 0, 0);
        h4 kd[6] = {};
        const uint32_t lA = pv + (mi >> 1) * 512 + (mi & 1) * 128 + r8 * 16, lB = pv + (2 + mi) * 512 + r8 * 16;
        const uint32_t lC = pv + (6 + (mi & 1)) * 512 + (mi >> 1) * 128 + r8 * 16, lF = pv + 4096 + (mi & 1) * 64 + (mi >> 1) * 16;
        const uint32_t sF = pv + 4096 + lane * 2;
        bar_sync(6, 288);
        asm volatile("setmaxnreg.inc.sync.aligned.u32 %0;" ::"n"(RM));
        const float dt = bfr(ex2(bf_lo(ldt + (lane & Z)) * LOG2E));
        uint32_t mx2 = __vmaxu2(__vmaxu2(vR.x & 0x7fff7fffu, vR.y & 0x7fff7fffu), __vmaxu2(vC.x & 0x7fff7fffu, vC.y & 0x7fff7fffu));
        const int ex = min(max(max((int)((__reduce_max_sync(~0u, max(mx2 >> 16, mx2 & 0xffffu)) >> 7) + (__float_as_uint(dt) >> 23)), (int)((Dsk >> 7) & 255) + 109), 140), 369);
        const float cs = dt * __uint_as_float((387 - ex) << 23), dl = -dt * LOG2E, ncs = __uint_as_float(__float_as_uint(cs) ^ 0x80000000u ^ Z);
        TS(w == 0 ? 0 : 63); T2S(0);
        auto gen = [&](uint32_t sel) {
            const float a2 = bfr(ex2(__uint_as_float(__byte_perm(vA.x, vA.y, sel) & 0xffff0000u) * LOG2E)) * dl;
            const float be = __uint_as_float(__byte_perm(vI.x, vI.y, sel) & 0xffff0000u) * dt;
            const cf wv = {__uint_as_float(__byte_perm(vR.x, vR.y, sel) & 0xffff0000u) * cs, __uint_as_float(__byte_perm(vC.x, vC.y, sel) & 0xffff0000u) * ncs};
            const cf y1 = cexp(a2, -be, 1.f), y2 = csq(y1), y4 = csq(y2), z8 = csqc(y4), z16 = csq(z8), z32 = csq(z16);
            const cf z64 = cexp(a2, be, 64.f);
            {
                const uint32_t f = pk_h(z64) ^ Z, f16 = pk_h(z16);
                const ch2 m0 = {pk_h(1.f, z32.r), pk_h(0.f, z32.i)}, m1 = hmul(m0, pk_h(z8));
                sts_ch2(st, m0, m1, hmul(m0, f16), hmul(m1, f16));
                sts16(sF, f); sts16(sF + 64, f >> 16);
            }
            if (KV & 4) sched_fence(Z);
            {
                const cf w4 = cmul(wv, y4), y256 = csqc(csq(z64)), y512 = csq(y256);
                const uint32_t f2 = pk_h(y2), f256 = pk_h(y256), f512 = pk_h(y512);
                const ch2 p0 = {pk_h(wv.r, w4.r), pk_h(wv.i, w4.i)};
                const ch2 p1 = hmul(p0, pk_h(y1)), p2 = hmul(p0, f2), p4 = hmul(p0, pk_h(y4));
                sts_ch2(st + 1024, p1, p2, hmul(p1, f2), p4);
                if (KV & 8) sched_fence(Z);
                const ch2 e1 = hmul(p4, f256);
                sts_ch2(st + 2048, hmul(p2, f256), e1, hmul(p4, f512), hmul(e1, f512));
                const ch2 g0 = {__byte_perm(p4.r, e1.r, 0x7632), __byte_perm(p4.i, e1.i, 0x7632)}, s0 = hmul(g0, pk_h(csq(y512)));
                sts_ch2(st + 3072, s0, hmul(s0, f512), p0, g0);
            }
            __syncwarp();
        };
        auto mul = [&]() {
#pragma unroll
            for (int k2 = 0; k2 < 2; k2++) {
                const uint4 M = ldsm4t(lA + k2 * 256), F = ldsm4(lF + k2 * 32);
                uint4 B[3];
                B[0] = ldsm4t(lB + k2 * 256); B[1] = ldsm4t(lB + k2 * 256 + 128); B[2] = ldsm4t(lC + k2 * 256);
#pragma unroll
                for (int i = 1; i >= 0; i--) {
                    const uint32_t fr = i ? F.z : F.x, fi = i ? F.w : F.y;
                    const ch2 m0 = {i ? M.y ^ Z : (KV & 1) ? M.x ^ Z : M.x, i ? M.w ^ Z : (KV & 1) ? M.z ^ Z : M.z}, m1 = hmul<1>(m0, fr, fi), m2 = hmul<0>(m1, fr, fi), m3 = hmul<1>(m2, fr, fi);
                    const uint4 A0 = make_uint4(m0.r, m1.r, m0.i, m1.i), A1 = make_uint4(m2.r, m3.r, m2.i, m3.i);
                    if (KV & 2) sched_fence(Z);
                    mma_h(kd[0], A0, B[i].x, B[i].y); mma_h(kd[1], A0, B[i].z, B[i].w); mma_h(kd[2], A0, i ? B[2].z : B[2].x, i ? B[2].w : B[2].y);
                    mma_h(kd[3], A1, B[i].x, B[i].y); mma_h(kd[4], A1, B[i].z, B[i].w); mma_h(kd[5], A1, i ? B[2].z : B[2].x, i ? B[2].w : B[2].y);
                }
            }
            __syncwarp();
        };
        gen(0x1044);
#pragma unroll 1
        for (uint32_t sel = 0x3244; sel < 0x8000; sel += 0x2200) {
            mul();
            gen(sel);
        }
        mul();
        TS(w == 0 ? 59 : w == 4 ? 60 : 63); T2S(1);
        {
#pragma unroll
            for (int nt = 0; nt < 3; nt++) stsm4(pv + (mi * 8 + (r8 >> 1) + (r8 & 1) * 4) * 16 + nt * 1056, kd[nt][0], kd[nt][1], kd[nt + 3][0], kd[nt + 3][1]);
            sts128(st + (lane < 4 ? P_TAB : P_TAB + (T1 + 518 - 16) * 4), 0, 0, 0, 0);
            sts32(cyP + 512, 0);
            __syncwarp();
            uint4 R0 = lds128(st), R1 = lds128(st + 1056), R2 = lds128(st + 2112);
            R0.x = hscl(R0.x); R0.y = hscl(R0.y); R0.z = hscl(R0.z); R0.w = hscl(R0.w);
            R1.x = hscl(R1.x); R1.y = hscl(R1.y); R1.z = hscl(R1.z); R1.w = hscl(R1.w);
            R2.x = hscl(R2.x); R2.y = hscl(R2.y); R2.z = hadd(hscl(R2.z), pk_h(bf_lo(Dsk) * __uint_as_float((370 - ex) << 23), 0.f));
            const bool l31 = lane == 31, l2 = lane < 2;
            uint32_t nx = __shfl_down_sync(~0u, R0.x, 1);
            if (l31) nx = R0.w >> 16;
            const uint32_t pr = __shfl_sync(~0u, l31 ? R0.w : R1.y, lane - 1);
            const uint32_t sA = __shfl_sync(~0u, R1.z, lane - 2), sB = __shfl_sync(~0u, R1.w, lane - 2);
            const uint32_t s0 = __shfl_sync(~0u, R2.x, lane - 2), s1 = __shfl_sync(~0u, R2.y, lane - 2);
            uint32_t a = tb + lane * 32;
            sts128(a + (T1 + 2) * 4, __byte_perm(R0.y, R0.x, 0x5410), __byte_perm(R0.z, R0.y, 0x5410), __byte_perm(R0.w, R0.z, 0x5410), __byte_perm(R0.x, R0.w, 0x5432));
            sts128(a + (T1 + 6) * 4, __byte_perm(R0.y, R0.x, 0x7632), __byte_perm(R0.z, R0.y, 0x7632), __byte_perm(R0.w, R0.z, 0x7632), __byte_perm(R0.w, nx, 0x3254));
            const uint32_t d1 = __byte_perm(R1.y, 0, 0x1010), d3 = __byte_perm(R1.y, 0, 0x3232);
            sts128(a + (T1 + 258) * 4, __byte_perm(pr, R1.x, 0x3254), __byte_perm(R1.y, R1.x, 0x5410), d1, d1);
            sts128(a + (T1 + 262) * 4, __byte_perm(R1.x, R1.y, 0x5432), __byte_perm(R1.y, R1.x, 0x7632), d3, d3);
            a = tb + T2 * 4 + (lane & 1) * 320 + (lane >> 1) * 8;
            const uint32_t pA = l2 ? 0 : sA, pB = l2 ? sA : sB, pT = l2 ? sB : 0;
            sts64(a, __byte_perm(R1.z, pA, 0x5410), __byte_perm(R1.z, pA, 0x7632));
            sts64(a + 128, __byte_perm(R1.w, pB, 0x5410), __byte_perm(R1.w, pB, 0x7632));
            if (lane < 16) sts64(a + 256, pT << 16, pT & 0xffff0000u);
            a = tb + T3 * 4 + lane * 4;
            const uint32_t p0 = __byte_perm(0, s0, l2 ? 0x5432 : 0x7654), p1 = __byte_perm(s0, s1, l2 ? 0x5432 : 0x7654);
            sts32(a, __byte_perm(R2.x, p0, 0x5410)); sts32(a + 128, __byte_perm(R2.x, p0, 0x7632));
            sts32(a + 256, __byte_perm(R2.y, p1, 0x5410)); sts32(a + 384, __byte_perm(R2.y, p1, 0x7632));
            if (lane == 0) sts128(tb + (T1 - 2) * 4, 0, 0, R2.z & 0xffffu, __byte_perm(R0.x, R2.z, 0x5410));
            if (l31) {
                sts128(tb + (T1 + 514) * 4, d3, d3 << 16, 0, 0);
                sts128(tb + (T4 + 3) * 4, R1.w >> 16, __byte_perm(R1.w, 0, 0x3232), R1.w & 0xffff0000u, 0);
            }
        }
        __syncwarp();
        TS(w == 0 ? 1 : 63); T2S(9);
        h4 acc[16] = {};
        const uint32_t dd = g - 2 * c;
        uint32_t a1 = tb + T1 * 4 + dd * 4, t2 = tb + T2 * 4 + dd * 8, aB = rw + r8 * BS + (mi >> 1) * TS8 + (mi & 1) * 16, ac0 = rw + lane * BS;
        uint32_t fa = pv + 16 + r8 * 16 + mi * 528, fb = fa + ((mi & 1) ? -528 : 512), fc = (mi < 2 ? fa : fb) + 4 * 528, fo = st + 16;
        uint32_t yb = sb + O_STG + 256 + w * 528 + (lane & 15) * 16, ya = (mi >> 1) == rk ? aB - TS8 : yb;
        uint32_t yc = pb + O_STG + r8 * 528 + w * 32 + (mi & 1) * 16 + (mi >> 1) * 2 * TS8, yd = pb + B_Y;
        uint32_t Id = (dd >> 1) ? 0 : 0x3c00 << (16 * (g & 1)), sc = (ex - 115) * 0x800080;
        yb += (mi >> 1) * 2 * TS8;
        pin4(a1, t2, aB, ac0, Z); pin4(fa, fb, fc, cyP, Z); pin4(yc, yd, ya, yb, Z);
        uint32_t Zr = Z;
        pin4(fo, Zr, Id, sc, Z);
        const uint32_t t3 = t2 + (T3 - T2) * 4;
        auto put_tiles = [&](int p) {
#pragma unroll
            for (int k = 0; k < 2; k++) {
                float d[4], e[4];
                mma_cvt(d, acc[4 * p + 2 * k], Id);
                mma_cvt(e, acc[4 * p + 2 * k + 1], Id);
                stsm4t(ya + (4 * p + 2 * k) * TS8, bmul(pk_bf(d[0], d[1]), sc), bmul(pk_bf(d[2], d[3]), sc), bmul(pk_bf(e[0], e[1]), sc), bmul(pk_bf(e[2], e[3]), sc));
            }
            __syncwarp();
            st_async(yc, lds128(yb + p * 4 * TS8), yd);
            yc += 4 * TS8; yd += 8;
            mbar_expect_e(sb + B_Y + p * 8, 512);
        };
        auto filter = [&](int p) {
            const uint32_t ac = ac0 + p * 4 * TS8;
            const uint4 q2 = lds128(ac), q3 = lds128(ac + 16);
            const uint32_t cy = lds32(cyP + 512);
            const uint2 q0 = lds64(ac - BS + 8);
            const uint4 q1 = lds128(ac - BS + 16);
            __syncwarp();
            if (!ORD || p == 2) put_tiles(p);
            sts32(cyP, cy);
            const uint32_t U[13] = {q0.x, q0.y, q1.x, q1.y, q1.z, q1.w, q2.x, q2.y, q2.z, q2.w, q3.x, q3.y, q3.z};
            uint32_t Q[13], Pp[12], P4[12], C3[12], C5[10];
#pragma unroll
            for (int k = 1; k < 13; k++) Q[k] = __byte_perm(U[k - 1], U[k], 0x5432);
#pragma unroll
            for (int k = 1; k < 12; k++) Pp[k] = hadd(U[k], Q[k]);
#pragma unroll
            for (int k = 2; k < 12; k++) P4[k] = hadd(Pp[k], Pp[k - 1]);
#pragma unroll
            for (int k = 3; k < 12; k++) C3[k] = hadd(Pp[k], Q[k + 1]);
#pragma unroll
            for (int k = 1; k < 10; k++) C5[k] = hadd(P4[k + 1], U[k - 1]);
            if (p < 2)
#pragma unroll
                for (int h = 0; h < 2; h++) {
                    const int k = 2 + 4 * h;
                    sts128(fo + (4 + h) * 528, hadd(P4[k], C3[k + 1]), hadd(P4[k + 1], C3[k + 2]), hadd(P4[k + 2], C3[k + 3]), hadd(P4[k + 3], C3[k + 4]));
                    sts128(fo + (6 + h) * 528, hadd(P4[k + 2], C5[k - 1]), hadd(P4[k + 3], C5[k]), hadd(P4[k + 4], C5[k + 1]), hadd(P4[k + 5], C5[k + 2]));
                }
            sts128(fo, C3[4], C3[5], C3[6], C3[7]); sts128(fo + 528, C3[8], C3[9], C3[10], C3[11]);
            sts128(fo + 2 * 528, C5[2], C5[3], C5[4], C5[5]); sts128(fo + 3 * 528, C5[6], C5[7], C5[8], C5[9]);
            __syncwarp();
        };
        uint2 T[5], U2[5], V[8];
        auto coarse = [&](int p, bool load) {
            if (load)
#pragma unroll
                for (int D = 0; D < 5; D++) if (p < 2 || D < 4) T[D] = lds64(t2 + D * 64);
#pragma unroll
            for (int gl = 0; gl < 4; gl++) {
                const uint4 A = ldsm4t(fa + gl * 128);
#pragma unroll
                for (int D = 0; D < 5; D++) if (4 * p + gl + D + 4 < 16) mma_h(acc[4 * p + gl + D + 4], A, T[D].x, T[D].y);
            }
            if (load) {
#pragma unroll
                for (int D = 0; D < 5; D++) if (p < 2 || D < 4) U2[D] = lds64(t2 + 320 + D * 64);
#pragma unroll
                for (int D = 0; D < 8 - 4 * p; D++) V[D] = lds64(t3 + D * 64);
            }
#pragma unroll
            for (int gl = 0; gl < 4; gl++) {
                const uint4 A = ldsm4t(fb + gl * 128);
#pragma unroll
                for (int D = 0; D < 5; D++) if (4 * p + gl + D + 4 < 16) mma_h(acc[4 * p + gl + D + 4], A, U2[D].x, U2[D].y);
                if (p < 2) {
                    const uint4 A3 = ldsm4t(fc + gl * 128);
#pragma unroll
                    for (int D = 7; D >= 0; D--) if (4 * p + gl + D + 8 < 16) mma_h(acc[4 * p + gl + D + 8], A3, V[D].x, V[D].y);
                }
            }
        };
        T2S(10);
        if (!ORD) conv_half<true>(acc, a1, aB, ac0 - BS + 16, sb + B_RAW, Zr);
        else mbar_wait(sb + B_RAW);
        T2S(11);
        filter(0);
        coarse(0, true);
        filter(1);
        coarse(1, false);
        T2S(12);
        if (ORD) {
            conv_half<true>(acc, a1, aB, ac0 - BS + 16, sb + B_RAW, Zr);
            __syncwarp();
            put_tiles(0);
            put_tiles(1);
        }
        T2S(22);
        conv_half<false>(acc, a1, aB + 8 * TS8, ac0 - BS + 16 + 8 * TS8, sb + B_RAW + 8, Zr);
        T2S(23);
        filter(2);
        coarse(2, true);
        put_tiles(3);
        T2S(24);
        TS(w == 0 ? 3 : (w == 7 ? 4 : 63));
        TDUMP;
    } else if (w < 16) {
        LANES;
        const int hw = w - 8, n0 = 8 * rk + hw;
        if (RH < 96) asm volatile("setmaxnreg.dec.sync.aligned.u32 %0;" ::"n"(RH));
        if (RH > 96) asm volatile("setmaxnreg.inc.sync.aligned.u32 %0;" ::"n"(RH));
        uint32_t tag;
        asm volatile("ld.relaxed.gpu.global.u32 %0,[%1];" : "=r"(tag) : "l"(prm.S->epoch + b) : "memory");
        tag = ~tag << 31;
        {
            uint32_t W[16];
#pragma unroll
            for (int k = 0; k < 4; k++) {
                const uint4 v = ldg128(prm.wr + hw * 16 + (k ^ (g & 1)) * 4 + c);
                W[4 * k] = v.x; W[4 * k + 1] = v.y; W[4 * k + 2] = v.z; W[4 * k + 3] = v.w;
            }
#pragma unroll
            for (int k = 0; k < 16; k++) if (g & 2) W[k] = 0x3f803f80u;
            const bool dg = mi == c, od = g & 1;
            uint32_t ra = sb + O_ROWS + g * 2048 + hw * 256 + od * 64 + c * 16;
            uint32_t pa = sb + O_XSEL + ((dg ? 0 : 8 + 4 * (g & 2)) + 2 * c + od) * 48 + hw * 4;
            TS(hw == 4 ? 22 : 63);
            bar_sync(3, 288);
#pragma unroll 1
            for (int hf = 0; hf < 2; hf++) {
                float d[4] = {}, e[4] = {};
                mbar_wait(sb + B_ROW + hf * 8);
                TS(hw == 4 ? (hf ? 23 : 58) : 63);
#pragma unroll
                for (int k = 0; k < 4; k++) {
                    const uint4 x = lds128((ra ^ ((k & 1) << 6)) + (k >> 1) * 128);
                    mma_bf(d, x.x ^ Z, W[4 * k], x.y ^ Z, W[4 * k + 1], x.x, x.y);
                    mma_bf(e, x.z ^ Z, W[4 * k + 2], x.w ^ Z, W[4 * k + 3], x.z, x.w);
                }
#define PICK2(e) (dg ? (od ? e[1] : e[0]) : (od ? e[3] : e[2]))
                sts32(pa, __float_as_uint(PICK2(d) + PICK2(e)));
                TS(hf ? 63 : 8 + hw);
                bar_arrive(1 + 3 * hf, 288);
                ra += 16384; pa += 1152;
            }
        }
        const uint32_t xa = sb + O_XT + hw * 512 + lane * 16;
        const bool ownr = ((r8 >> 1) & 1) == rk;
        const uint32_t ta = sb + (ownr ? O_RAW + n0 * BS : O_STG + hw * 528) + (mi ^ 1) * 64 + (r8 & 1) * 32 + (r8 >> 2) * 16;
        const uint32_t ca = (lane & 15) * 16 + (lane >> 4) * 2 * TS8;
        const uint2* sp = prm.S->stats + (q & 1) * 2048 + n0 * 16 + (lane & 2) * 4 + g;
        uint4 x[8];
        uint2 u[8];
        uint32_t G[32];
        float h[32];
        auto load = [&](int hf) {
            mbar_wait(sb + B_X + hf * 8);
#pragma unroll
            for (int i = 4 * hf; i < 4 * hf + 4; i++) x[i] = lds128(xa + i * 2 * TS8);
        };
        auto poll = [&](int hf) {
            mbar_wait(sb + B_GO + hf * 8);
            TS(hw == 3 ? 16 + hf : 63);
            const uint2* v = u + 4 * hf;
            int it = 0;
#pragma unroll 1
            do {
#pragma unroll
                for (int i = 4 * hf; i < 4 * hf + 4; i++) u[i] = ldr64(sp + i * 256);
            } while (__any_sync(~0u, (int)(((v[0].x ^ tag) | (v[1].x ^ tag)) | ((v[2].x ^ tag) | (v[3].x ^ tag))) < 0) && ++it < 100000);
            TV(hw == 7 ? 61 + hf : 63, it);
            TS(hw == 3 ? (hf ? 25 : 18) : 63);
        };
        auto norm = [&](int i0) {
#pragma unroll
            for (int i = i0; i < i0 + 2; i++) {
                const float r = fabsf(__uint_as_float(u[i].x));
                float* v = h + 8 * (i & 3);
#pragma unroll
                for (int k = 0; k < 4; k++) {
                    const uint32_t e = bsub_lo(comp(x[i], k), u[i].y);
                    v[2 * k] = bf_lo(e) * r; v[2 * k + 1] = bf_hi(e) * r;
                }
                stsm4t(ta + i * 2 * TS8, pk_h(v[2], v[3]), pk_h(v[0], v[1]), pk_h(v[6], v[7]), pk_h(v[4], v[5]));
            }
            __syncwarp();
            st_async(pb + O_RAW + n0 * BS + ca + i0 * 2 * TS8, lds128(sb + O_STG + hw * 528 + ca + i0 * 2 * TS8), pb + B_RAW + (i0 & 4) * 2);
            if (i0 & 2) mbar_expect_e(sb + B_RAW + (i0 & 4) * 2, 1024);
        };
        auto gate = [&](int i0) {
            uint32_t* v = G + 4 * i0;
            const float* e = h + 8 * (i0 & 3);
#pragma unroll
            for (int k = 0; k < 8; k++) v[k] = pk_bf(fmaf(e[2 * k], ftanh(e[2 * k]), e[2 * k]), fmaf(e[2 * k + 1], ftanh(e[2 * k + 1]), e[2 * k + 1]));
            pin4(v[0], v[1], v[2], v[3], Z); pin4(v[4], v[5], v[6], v[7], Z);
        };
        asm volatile("barrier.cluster.wait.aligned;" ::: "memory");
        load(0); poll(0); norm(0); norm(2);
        TS(32 + hw);
        sched_fence(Z);
        gate(0); gate(2);
        TS(hw == 0 ? 20 : 63);
        load(1); poll(1); norm(4); gate(4);
        sched_fence(Z);
        norm(6);
        TS(hw == 3 ? 19 : 63);
        gate(6);
        TS(hw == 0 ? 21 : 63);
        if (RH2 < RH) asm volatile("setmaxnreg.dec.sync.aligned.u32 %0;" ::"n"(RH2));
        mbar_wait(sb + B_SEL);
        mbar_wait(sb + B_SEL + 8);
        if (hw == 0) { mbar_wait(sb + B_RAW); if (lane == 0) prm.S->epoch[b] = lds32(sb + O_SEL + 16); }
        const uint32_t tok = n0 * 16 + (lane & 2) * 4 + g, r0 = lds32(sb + O_SEL) - tok, r1 = lds32(sb + O_SEL + 8) - tok;
        const uint32_t mine = ((r0 & 255) ? 0 : 128 << (r0 >> 8)) | ((r1 & 255) ? 0 : 128 << (r1 >> 8));
        const uint32_t skip = __reduce_or_sync(~0u, mine), dir = (skip | 128 << NSTG | 256 << NSTG) & ~mine;
        const uint32_t sa = ownr ? ta - TS8 : ta;
        uint4* op = prm.out + tok * 128 + q * 2 + (lane & 1);
#pragma unroll
        for (int p = 0; p < 4; p++) {
            mbar_wait(sb + B_Y + p * 8);
#pragma unroll
            for (int i = 2 * p; i < 2 * p + 2; i++) {
                const uint4 s = ldsm4t(sa + i * 2 * TS8);
                const uint4 o = make_uint4(bfma(s.y, G[4 * i], x[i].x), bfma(s.x, G[4 * i + 1], x[i].y), bfma(s.w, G[4 * i + 2], x[i].z), bfma(s.z, G[4 * i + 3], x[i].w));
                asm volatile("{.reg .pred p; setp.ne.u32 p,%5,0; @p st.global.v4.u32 [%0],{%1,%2,%3,%4};}" ::"l"(op + i * 32768), "r"(o.x), "r"(o.y), "r"(o.z), "r"(o.w), "r"(dir & 128 << i) : "memory");
                if (i < NSTG) asm volatile("{.reg .pred p; setp.eq.u32 p,%5,0; @p st.shared.v4.u32 [%0],{%1,%2,%3,%4};}" ::"r"(xa + i * 2 * TS8), "r"(o.x), "r"(o.y), "r"(o.z), "r"(o.w), "r"(skip & 128 << i) : "memory");
            }
            if (2 * p < NSTG) {
                fence_async();
                __syncwarp();
#pragma unroll
                for (int i = 2 * p; i < 2 * p + 2; i++) tma4d_st_e(sb + O_XT + hw * 512 + i * 2 * TS8, &mo, q * 16, n0 + 16 * i + ((skip >> i) & 128));
            }
        }
        asm volatile("cp.async.bulk.commit_group; cp.async.bulk.wait_group.read 0;" ::: "memory");
        TS(40 + hw);
        TDUMP;
    } else {
        asm volatile("setmaxnreg.dec.sync.aligned.u32 %0;" ::"n"(480 - 2 * RM - 2 * RH));
        LANES;
        const int fw = w - 16;
        const CUtensorMap* m1 = &mg + rk;
        if (fw == 0) {
            bar_arrive(5, 128);
            spin(t0 + ROW1 + ((b * ROWD) >> 7));
            bulk_e(sb + O_ROWS + 16384, prm.u + (128 + b) * 1024, sb + B_ROW + 8, 16384);
            bar_sync(7, 64);
            if (b < NFFN) {
#pragma unroll 1
                for (int i = 0; i < NPF; i++) {
                    spin(t0 + W0 + ((b * WD) >> 7) + i * WD);
                    if (i == RING - 4) mbar_wait(sb + B_P1);
                    if (i < RING) tma3d_e(sb + O_RING + i * 8192, m1, i * 64, q, sb + B_FULL + i * 8);
                    else asm volatile("{.reg .pred p; elect.sync _|p,0xffffffff; @p cp.async.bulk.prefetch.tensor.3d.L2.global [%0,{0,%1,%2}];}" ::"l"(m1), "r"(i * 64), "r"(q) : "memory");
                }
            }
        } else {
            if (lane == 0) {
#pragma unroll
                for (int i = 0; i < 15; i++)
                    asm volatile("mbarrier.init.shared.b64 [%0],%1;" ::"r"(sb + B_FULL - 8 + 8 * fw + i * 24), "r"(i < 11 ? 1 : 8) : "memory");
            }
            __syncwarp();
            asm volatile("fence.mbarrier_init.release.cluster; barrier.cluster.arrive.relaxed.aligned;" ::: "memory");
            asm volatile("prefetch.tensormap [%0];" ::"l"(&md - 1 + fw));
            asm volatile("prefetch.tensormap [%0];" ::"l"(m1));
            bar_sync(5, 128);
            if (fw == 1) {
                bar_arrive(3, 288);
                bar_arrive(6, 288);
                bar_arrive(7, 64);
                mbar_expect_e(sb + B_H, 256);
                mbar_expect_e(sb + B_X, 16384);
                mbar_expect_e(sb + B_X + 8, 16384);
#pragma unroll 1
                for (int i = 0; i < 8; i++) {
                    spin(t0 + (i < 4 ? GAT0 : GAT1) + (i & 3) * GATD);
                    tma4d_e(sb + O_XT + i * 2 * TS8, &mx, q * 16, i * 16 + rk * 8, sb + B_X + (i & 4) * 2);
                }
            }
        }
        if (fw == 2) {
            spin(t0 + TGO0);
            mbar_arrive_e(sb + B_GO);
        }
        if (fw == 3) {
            uint32_t ep;
            asm volatile("ld.relaxed.gpu.global.u32 %0,[%1];" : "=r"(ep) : "l"(prm.S->epoch + b) : "memory");
            ep += 1;
            sts32(sb + O_SEL + 16, ep);
            float sw[4] = {0.f, 0.f, 0.f, 0.f};
#pragma unroll
            for (int k = 0; k < 4; k++) mma_bf(sw, ldg128(prm.wr + k * 32 + lane), 0x3f803f80u, 0x3f803f80u);
            float wsum = sw[0] + sw[2];
#pragma unroll
            for (int o = 4; o < 32; o <<= 1) wsum += __shfl_xor_sync(~0u, wsum, o);
            uint2* dst = prm.S->stats + (lane & 1) * 2048 + b * 8 + g;
            uint32_t pa = sb + O_XSEL + g * 48 + (lane & 1) * 16, ky = 0;
            const uint32_t id = (ep & 1) * 0x8000 + 2047 - (lane & 1) * 1024 - b * 8 - g;
#pragma unroll 1
            for (int hf = 0; hf < 2; hf++) {
                bar_sync(1 + 3 * hf, 288);
                float v[3];
#pragma unroll
                for (int k = 0; k < 3; k++) {
                    const uint4 t = lds128(pa + k * 384);
                    v[k] = (__uint_as_float(t.x) + __uint_as_float(t.y)) + (__uint_as_float(t.z) + __uint_as_float(t.w));
                    v[k] += __shfl_xor_sync(~0u, v[k], 1);
                }
                const float mean = v[2] * (1.f / 1024.f);
                const float var = fmaxf(fmaf(-mean, mean, v[0] * (1.f / 1024.f)), 0.f);
                const float rs = rcp(bfr(fsqrt(bfr(bfr(var) + 1e-5f))));
                const uint32_t mk = pk_bf(mean, fmaf(-bfr(mean), wsum, v[1]) * rs);
                str64(dst, __float_as_uint(0.5f * rs) | ep << 31, mk);
                if ((lane & 1) == hf) ky = ((mk ^ (((int)mk >> 31) | 0x80000000u)) & 0xffff0000u) | id;
                TS(hf ? 63 : 5);
                dst += 1024; pa += 1152;
            }
            const uint32_t k1 = __reduce_max_sync(~0u, ky), k2 = __reduce_max_sync(~0u, ky == k1 ? 0u : ky);
            str64(prm.S->keys + g * 128 + b, k1, k2);
            TS(48);
            mbar_arrive_e(sb + B_P1);
        }
        uint32_t wa[4];
#pragma unroll
        for (int i = 0; i < 4; i++) wa[i] = pin(sb + O_RING + fw * 8192 + ((mi >> 1) * 8 + r8) * 128 + (((2 * i + (mi & 1)) ^ r8) << 4));
        uint32_t xs = pin(sb + O_XSEL + fw * 128 + (r8 & 1) * 2064 + mi * 16);
        if (fw >= 2) {
            const uint2* kp = prm.S->keys + ((b & 3) * 2 + (fw & 1)) * 128 + lane * 2;
            mbar_wait(sb + B_P1);
            const uint32_t tag = lds32(sb + O_SEL + 16) << 15;
            spin(t0 + TTOP);
            uint4 k, l;
            int it = 0;
#pragma unroll 1
            do { k = ldr128(kp); l = ldr128(kp + 64); } while (__any_sync(~0u, (((k.x ^ tag) | (k.z ^ tag)) | ((l.x ^ tag) | (l.z ^ tag))) & 0x8000) && ++it < 100000);
            TV(fw == 2 ? 24 : 63, it);
            TS(fw == 2 ? 49 : 63);
            if (fw == 2) mbar_arrive_e(sb + B_GO + 8);
            uint32_t ky = __reduce_max_sync(~0u, max(max(k.x, k.z), max(l.x, l.z)));
            if (fw & 1) ky = __reduce_max_sync(~0u, max(max(k.x == ky ? k.y : k.x, k.z == ky ? k.w : k.z), max(l.x == ky ? l.y : l.x, l.z == ky ? l.w : l.z)));
            const uint32_t tok = ~ky & 2047;
            uint4 v[4];
#pragma unroll
            for (int j = 0; j < 4; j++) v[j] = ldg128(prm.u + tok * 128 + j * 32 + lane);
            uint2 rc;
#pragma unroll 1
            do rc = ldr64(prm.S->stats + (q & 1) * 2048 + tok); while ((int)(rc.x ^ tag << 16) < 0 && ++it < 100000);
            const uint32_t rsel = pk_bf(0.f, sigm(bf_hi(ky ^ (~((int)ky >> 31) | 0x80000000u))));
            const float rs = 2.f * fabsf(__uint_as_float(rc.x));
            const uint32_t r = pk_bf(rs, rs - bfr(rs));
#pragma unroll
            for (int j = 0; j < 4; j++)
                sts128(sb + O_XSEL + (fw & 1) * 2064 + j * 512 + lane * 16, norm2(v[j].x, rc.y, r), norm2(v[j].y, rc.y, r), norm2(v[j].z, rc.y, r), norm2(v[j].w, rc.y, r));
            if (lane == 0) sts64(sb + O_SEL + (fw & 1) * 8, tok, rsel);
            __syncwarp();
            mbar_arrive_e(sb + B_SEL + (fw & 1) * 8);
        }
        if (RF2 > 480 - 2 * RM - 2 * RH) asm volatile("setmaxnreg.inc.sync.aligned.u32 %0;" ::"n"(RF2));
        mbar_wait(sb + B_SEL);
        mbar_wait(sb + B_SEL + 8);
        const uint32_t ep = lds32(sb + O_SEL + 16);

        TS(fw == 1 ? 50 : 63);
        if (b < NFFN) {
            float h[4][4];
#pragma unroll
            for (int i = 0; i < 4; i++) { h[i][0] = h[i][1] = h[i][2] = h[i][3] = 0.f; }
            const bool c1 = c & 1, c2 = c & 2;
            uint4* dst = prm.S->yp + ((rk * 32 + fw * 4 + c) * 64 + q) * 8 + g;
#define PICK(k) __float_as_uint(c2 ? (c1 ? h[3][k] : h[2][k]) : (c1 ? h[1][k] : h[0][k]))
#pragma unroll 1
            for (int n = 0; n < 6; n++) {
                const int so = (n & 1) * 32768, i = fw + 4 * n;
                mbar_wait(sb + B_FULL + i * 8);
                TS(64 + i);
#pragma unroll
                for (int hf = 0; hf < 2; hf++) {
                    uint4 A[8];
                    const uint4 B = ldsm4(xs + hf * 64);
#pragma unroll
                    for (int k = 0; k < 8; k++) A[k] = ldsm4t(wa[k & 3] + so + hf * 4096 + (k >> 2) * 2048);
                    sched_fence(Z);
#pragma unroll
                    for (int k = 0; k < 8; k++) mma_bf(h[k & 3], A[k], k < 4 ? B.x : B.z, k < 4 ? B.y : B.w);
                }
                TS(96 + i);
                if (n < 4) {
                    sched_fence(Z);
                    if (n < PACE) spin(t0 + W0 + ((b * WD) >> 7) + (i + 8) * WD);
                    tma3d_e(sb + O_RING + fw * 8192 + so, n < 2 ? m1 : &md, (n < 2 ? i + 8 : q) * 64, n < 2 ? q : rk * 8 + i - 8, sb + B_FULL + i * 8 + 64);
                    xs += 512;
                    if (n < 3) continue;
                }
                const uint4 o = make_uint4(PICK(0), PICK(1), PICK(2), PICK(3));
#pragma unroll
                for (int k = 0; k < 4; k++) { h[k][0] = h[k][1] = h[k][2] = h[k][3] = 0.f; }
                if (n > 3) {
                    str128(dst, make_uint4((o.x & ~1u) | (ep & 1), o.y, o.z, o.w));
                    dst += 16 * 64 * 8;
                    continue;
                }
                sts128(sb + O_PART + fw * 512 + lane * 16, o.x, o.y, o.z, o.w);
                bar_sync(2, 128);
                TS(fw == 0 ? 51 : 63);
                if (fw < 2) {
                    const uint32_t pa = sb + O_PART + (r8 * 4 + fw * 2 + (mi >> 1)) * 16 + (mi & 1) * 8;
                    const uint2 p0 = lds64(pa), p1 = lds64(pa + 512), p2 = lds64(pa + 1024), p3 = lds64(pa + 1536);
                    uint32_t v = pk_bf((__uint_as_float(p0.x) + __uint_as_float(p1.x)) + (__uint_as_float(p2.x) + __uint_as_float(p3.x)),
                                       (__uint_as_float(p0.y) + __uint_as_float(p1.y)) + (__uint_as_float(p2.y) + __uint_as_float(p3.y)));
                    if (rk == 0) v = pk_bf(silu(bf_lo(v)), silu(bf_hi(v)));
                    asm volatile("st.async.shared::cluster.mbarrier::complete_tx::bytes.b32 [%0],%1,[%2];" ::"r"(pb + O_HX + fw * 128 + lane * 4), "r"(v), "r"(pb + B_H) : "memory");
                    mbar_wait(sb + B_H);
                    v = bmul(v, lds32(sb + O_HX + fw * 128 + lane * 4));
                    sts16(sb + O_HT + fw * 64 + lane * 2, v); sts16(sb + O_HT + 144 + fw * 64 + lane * 2, v >> 16);
                }
                xs = sb + O_HT + (r8 & 1) * 144 + mi * 16;
                bar_sync(2, 128);
                TS(fw == 0 ? 52 : 63);
            }
            TS(fw == 0 ? 63 : 52 + fw);
        }
        const uint2 sel = lds64(sb + O_SEL + (lane & 1) * 8);
        const bool own = ((sel.x >> 7) & 1) == rk;
        if (!NOFIX && __any_sync(~0u, own)) {
            uint32_t xv;
            if (fw == 0) asm volatile("ld.global.nc.u16 %0,[%1];" : "=r"(xv) : "l"((const uint16_t*)prm.u + sel.x * 1024 + q * 16 + (lane >> 1)) : "memory");
            spin(t0 + TFIX);
            bar_sync(2, 128);
            const uint4* yp = prm.S->yp + q * 512 + fw * 32 + lane;
            float y[4];
            int it = 0;
            uint32_t bad;
#pragma unroll 1
            do {
                uint4 v[4];
#pragma unroll
                for (int j = 0; j < 3; j++) v[j] = ldr128(yp + j * 128);
                v[3] = make_uint4(ep & 1, 0, 0, 0);
                if (fw < 2) v[3] = ldr128(yp + 384);
                y[0] = y[1] = y[2] = y[3] = 0.f;
                bad = 0;
#pragma unroll
                for (int j = 0; j < 4; j++) {
                    y[0] += __uint_as_float(v[j].x); y[1] += __uint_as_float(v[j].y); y[2] += __uint_as_float(v[j].z); y[3] += __uint_as_float(v[j].w);
                    bad |= v[j].x ^ ep;
                }
            } while (__any_sync(~0u, bad & 1) && ++it < 100000);
            TV(fw == 0 ? 57 : 63, it);
            sts128(sb + O_PART + fw * 512 + lane * 16, __float_as_uint(y[0]), __float_as_uint(y[1]), __float_as_uint(y[2]), __float_as_uint(y[3]));
            bar_sync(2, 128);
            if (fw == 0) {
                const uint32_t pa = sb + O_PART + (lane & 14) * 8 + (lane >> 4) * 8 + (lane & 1) * 4;
                float t[2] = {0.f, 0.f};
#pragma unroll
                for (int j = 0; j < 16; j++) t[j & 1] += __uint_as_float(lds32(pa + j * 128));
                const float xn = bf_lo(lds16(sb + O_XSEL + (lane & 1) * 2064 + q * 32 + (lane >> 1) * 2));
                const float gt = bfr(silu(bfr(xn + bfr(bfr(t[0] + t[1]) * __uint_as_float(sel.y)))));
                TS(56);
                const uint32_t n = sel.x >> 4;
                const uint32_t sa = sb + ((lane >> 4) == rk ? O_RAW - TS8 + n * BS : O_STG + (n >> 4) * 2 * TS8 + (n & 7) * 528) + (lane & 14) * 16;
                mbar_wait(sb + B_Y + __reduce_max_sync(~0u, own ? n >> 5 : 0) * 8);
                if (own) ((uint16_t*)prm.out)[sel.x * 1024 + q * 16 + (lane >> 1)] = pk_bf(fmaf(bf_lo(lds16(sa + (sel.x & 15) * 2)), gt, bf_lo(xv)), 0.f);
                TS(7);
            }
        }
        TDUMP;
    }
}

typedef CUresult (*EncFn)(CUtensorMap*, CUtensorMapDataType, cuuint32_t, void*, const cuuint64_t*, const cuuint64_t*,
                          const cuuint32_t*, const cuuint32_t*, CUtensorMapInterleave, CUtensorMapSwizzle,
                          CUtensorMapL2promotion, CUtensorMapFloatOOBfill);

void make_map(EncFn f, CUtensorMap* m, const void* p, int rank, const cuuint64_t* gd, const cuuint64_t* gs,
              const cuuint32_t* bd, CUtensorMapSwizzle sw) {
    const cuuint32_t es[4] = {1, 1, 1, 1};
    f(m, CU_TENSOR_MAP_DATA_TYPE_BFLOAT16, rank, const_cast<void*>(p), gd, gs, bd, es, CU_TENSOR_MAP_INTERLEAVE_NONE, sw,
      CU_TENSOR_MAP_L2_PROMOTION_NONE, CU_TENSOR_MAP_FLOAT_OOB_FILL_NONE);
}

}

extern "C" void kernel_launch(void* const* d_in, const int* in_sizes, int n_in, void* d_out, int out_size) {
    (void)in_sizes; (void)n_in; (void)out_size;
    void* fp = nullptr;
    cudaDriverEntryPointQueryResult qr;
    cudaGetDriverEntryPoint("cuTensorMapEncodeTiled", &fp, cudaEnableDefault, &qr);
    EncFn enc = (EncFn)fp;
    Maps maps;
    CUtensorMap &mg = maps.m[0], &mu = maps.m[1], &md = maps.m[2], &mx = maps.m[3], &mo = maps.m[4];
    {
        const cuuint64_t gd[3] = {64, 1024, 56}, gs[2] = {7168, 128};
        const cuuint32_t bd[3] = {64, 64, 1};
        make_map(enc, &mg, d_in[9], 3, gd, gs, bd, CU_TENSOR_MAP_SWIZZLE_128B);
        make_map(enc, &mu, d_in[10], 3, gd, gs, bd, CU_TENSOR_MAP_SWIZZLE_128B);
    }
    {
        const cuuint64_t gd[3] = {64, 3584, 16}, gs[2] = {2048, 128};
        const cuuint32_t bd[3] = {64, 64, 1};
        make_map(enc, &md, d_in[11], 3, gd, gs, bd, CU_TENSOR_MAP_SWIZZLE_128B);
    }
    {
        const cuuint64_t gd[4] = {1024, 2, 8, 128}, gs[3] = {16384, 2048, 32768};
        const cuuint32_t bd[4] = {16, 2, 8, 8}, bo[4] = {16, 2, 8, 1};
        make_map(enc, &mo, d_out, 4, gd, gs, bo, CU_TENSOR_MAP_SWIZZLE_NONE);
        make_map(enc, &mx, d_in[0], 4, gd, gs, bd, CU_TENSOR_MAP_SWIZZLE_NONE);
    }
    Params p;
    p.u = (const uint4*)d_in[0]; p.logA = (const uint2*)d_in[1]; p.Aim = (const uint2*)d_in[2];
    p.Cre = (const uint2*)d_in[3]; p.Cim = (const uint2*)d_in[4];
    p.logdt = (const uint16_t*)d_in[5]; p.Dsk = (const uint16_t*)d_in[6]; p.wr = (const uint4*)d_in[8];
    p.out = (uint4*)d_out;
    void* sp = nullptr;
    cudaGetSymbolAddress(&sp, g_scratch);
    p.S = (Scratch*)sp; p.zero = 0;
    cudaFuncSetAttribute(fused_kernel, cudaFuncAttributeMaxDynamicSharedMemorySize, SMEM_BYTES + 512);
    fused_kernel<<<128, 640, SMEM_BYTES + 512, cudaStreamPerThread>>>(p, maps);
}
```

```cpp
#include <cuda_runtime.h>
#include <cuda_bf16.h>
#include <cuda_fp16.h>
#include <cuda.h>
#include <stdint.h>

#define RM 112
#define RH 88
#define ORD 0
#define FSB 1
#define RH2 RH
#define RF2 (480 - 2 * RM - 2 * RH2)
#define KV 1
#define FUNROLL 7
#define TKEEP 0
#define FM 1023
#define SBC 1
#define NOFIX 0
#define NFFN 112
namespace {

constexpr int RING = 8, FUN = FUNROLL;
constexpr uint32_t BS = 272, TS8 = 8 * BS;
constexpr uint32_t O_RING = 0;
constexpr uint32_t O_XT   = RING * 8192;
constexpr uint32_t O_RAW  = O_XT + 32768 + TS8;
constexpr uint32_t O_XB   = O_RAW + 8 * TS8 + 128;
constexpr uint32_t O_HX   = O_RAW + 16 * TS8;
constexpr uint32_t O_HT   = O_HX + 256;
constexpr uint32_t O_RNG3 = 133 * 1024;
constexpr uint32_t O_PST  = O_RNG3 + 3 * 8192;
constexpr uint32_t O_PRIV = O_RNG3 + 32768;
constexpr uint32_t PRIV   = 7744;
constexpr uint32_t P_TAB  = 4224;
constexpr uint32_t O_XSEL = O_XT + 6 * 4096;
constexpr uint32_t O_ROWS = (RING - 4) * 8192;
constexpr uint32_t O_SEL  = O_PRIV + 8 * PRIV;
constexpr uint32_t O_ONE  = O_SEL + 64;
constexpr uint32_t O_BAR  = O_ONE + 128;
constexpr uint32_t B_ROW = O_BAR, B_FULL = B_ROW + 16, B_H = B_FULL + 8 * 24, B_SEL = B_H + 8, B_P1 = B_SEL + 16,
                   B_X = B_P1 + 8, B_GO = B_X + 16, B_XS = B_GO + 16, B_XF = B_XS + 8, B_O = B_XF + 8, B_Y = B_O + 160, B_RAW = B_Y + 40, B_HR = B_RAW + 16, B_XR = B_HR + 8;
constexpr uint32_t SMEM_BYTES = B_Y + 72;
static_assert(B_Y - B_FULL == 18 * 24 && O_XB % 256 == 0 && O_HT + 288 <= O_RNG3 && O_XB + 32768 <= O_RNG3 + 16384, "layout");
static_assert(SMEM_BYTES + 512 <= 232448, "smem");
constexpr int PB = 1216, T2 = 2368, T3 = T2 + 640;

#define SCHED(X) X(0, ROW0, 250) X(1, ROW1, 950) X(2, NPE, 11) X(3, GAT0, 900) X(4, GAT1, 2000) X(5, GATD, 100) X(6, TGO0, 2750) \
    X(7, TTOP, 3850) X(8, W0, 1750) X(9, WD, 280) X(10, LEAD, 3) X(11, GATE, 500) X(13, TFIX, 10000) X(14, PACE, 3)
#define X(i, n, v) constexpr int n = v;

struct Scratch {
    uint2 stats[4 * 2048];
    uint2 keys[8 * 128];
    uint2 yp[128 * 56 * 8];
    unsigned epoch[128];
    int ts[128 * 128];
};
__device__ Scratch g_scratch;

struct Maps { CUtensorMap m[5]; };
struct Params {
    const uint4* u; const uint2* logA; const uint2* Aim; const uint2* Cre; const uint2* Cim;
    const uint16_t* logdt; const uint16_t* Dsk; const uint4* wr;
    uint4* out; Scratch* S; uint32_t zero;
};

#define DI __device__ __forceinline__
DI int lane_id() { int l; asm volatile("mov.u32 %0,%%laneid;" : "=r"(l)); __builtin_assume(l >= 0 && l < 32); return l; }
DI int now_ns() { int c; asm volatile("mov.u32 %0,%%globaltimer_lo;" : "=r"(c)::"memory"); return c; }
DI void spin(int t) {
    asm volatile("{.reg .pred p; .reg .s32 c; L: mov.u32 c,%%globaltimer_lo; sub.s32 c,c,%0; setp.lt.s32 p,c,0; @p nanosleep.u32 32; @p bra.uni L;}" ::"r"(t) : "memory");
}
DI void mbar_arrive_e(uint32_t b) { asm volatile("{.reg .pred p; elect.sync _|p,0xffffffff; @p mbarrier.arrive.shared.b64 _,[%0];}" ::"r"(b) : "memory"); }
DI void mbar_expect_e(uint32_t b, int tx) { asm volatile("{.reg .pred p; elect.sync _|p,0xffffffff; @p mbarrier.arrive.expect_tx.shared.b64 _,[%0],%1;}" ::"r"(b), "r"(tx) : "memory"); }
DI void mbar_wait(uint32_t b) {
    asm volatile("{.reg .pred p; W: mbarrier.try_wait.parity.shared.b64 p,[%0],0; @!p bra.uni W; }" ::"r"(b) : "memory");
}
DI void bulk_e(uint32_t dst, const void* src, uint32_t bar, int bytes) {
    asm volatile("{.reg .pred p; elect.sync _|p,0xffffffff; @p cp.async.bulk.shared::cluster.global.mbarrier::complete_tx::bytes [%0],[%1],%3,[%2];}" ::"r"(dst), "l"(src), "r"(bar), "r"(bytes) : "memory");
}
DI void tma3d_e(uint32_t dst, const CUtensorMap* m, int c1, int c2, uint32_t bar) {
    asm volatile("{.reg .pred p; elect.sync _|p,0xffffffff; @p mbarrier.arrive.expect_tx.shared.b64 _,[%2],8192;\n"
                 "@p cp.async.bulk.tensor.3d.shared::cluster.global.mbarrier::complete_tx::bytes [%0],[%1,{0,%3,%4}],[%2];}" ::"r"(dst), "l"(m), "r"(bar), "r"(c1), "r"(c2) : "memory");
}
DI void tma5d_mc_e(uint32_t dst, const CUtensorMap* m, int c0, int c2, uint32_t bar) {
    asm volatile("{.reg .pred p; elect.sync _|p,0xffffffff;\n"
                 "@p cp.async.bulk.tensor.5d.shared::cluster.global.mbarrier::complete_tx::bytes.multicast::cluster [%0],[%1,{%3,0,%4,0,0}],[%2],%5;}"
                 ::"r"(dst), "l"(m), "r"(bar), "r"(c0), "r"(c2), "h"((uint16_t)3) : "memory");
}
DI void tma5d_st_e(uint32_t src, const CUtensorMap* m, int c0, int c2, int c4) {
    asm volatile("{.reg .pred p; elect.sync _|p,0xffffffff; @p cp.async.bulk.tensor.5d.global.shared::cta.bulk_group [%1,{%2,0,%3,0,%4}],[%0];}" ::"r"(src), "l"(m), "r"(c0), "r"(c2), "r"(c4) : "memory");
}
DI void mbar_arrive_peer_e(uint32_t b) { asm volatile("{.reg .pred p; elect.sync _|p,0xffffffff; @p mbarrier.arrive.relaxed.cluster.shared::cluster.b64 _,[%0];}" ::"r"(b) : "memory"); }
DI void st_async(uint32_t dst, const uint4& v, uint32_t bar) {
    asm volatile("st.async.shared::cluster.mbarrier::complete_tx::bytes.v4.b32 [%0],{%1,%2,%3,%4},[%5];" ::"r"(dst), "r"(v.x), "r"(v.y), "r"(v.z), "r"(v.w), "r"(bar) : "memory");
}
DI void fence_async() { asm volatile("fence.proxy.async.shared::cta;" ::: "memory"); }
DI void bar_sync(int id, int n) { asm volatile("bar.sync %0,%1;" ::"r"(id), "r"(n) : "memory"); }
DI void bar_arrive(int id, int n) { asm volatile("bar.arrive %0,%1;" ::"r"(id), "r"(n) : "memory"); }
DI uint4 ldg128(const void* p) { uint4 v; asm volatile("ld.global.nc.v4.u32 {%0,%1,%2,%3},[%4];" : "=r"(v.x), "=r"(v.y), "=r"(v.z), "=r"(v.w) : "l"(p) : "memory"); return v; }
DI uint2 ldg64(const void* p) { uint2 v; asm volatile("ld.global.nc.v2.u32 {%0,%1},[%2];" : "=r"(v.x), "=r"(v.y) : "l"(p) : "memory"); return v; }
DI uint4 ldr128(const void* p) {
    uint4 v;
    asm volatile("{.reg .b128 t; .reg .b64 a,b; ld.relaxed.gpu.global.b128 t,[%4]; mov.b128 {a,b},t; mov.b64 {%0,%1},a; mov.b64 {%2,%3},b;}"
                 : "=r"(v.x), "=r"(v.y), "=r"(v.z), "=r"(v.w) : "l"(p) : "memory");
    return v;
}
DI uint2 ldr64(const void* p) { uint2 v; asm volatile("{.reg .b64 t; ld.relaxed.gpu.global.b64 t,[%2]; mov.b64 {%0,%1},t;}" : "=r"(v.x), "=r"(v.y) : "l"(p) : "memory"); return v; }
DI void str64(void* p, uint32_t x, uint32_t y) { asm volatile("{.reg .b64 t; mov.b64 t,{%1,%2}; st.relaxed.gpu.global.b64 [%0],t;}" ::"l"(p), "r"(x), "r"(y) : "memory"); }
DI uint32_t lds32(uint32_t a) { uint32_t v; asm volatile("ld.shared.u32 %0,[%1];" : "=r"(v) : "r"(a) : "memory"); return v; }
DI uint32_t lds16(uint32_t a) { uint32_t v; asm volatile("ld.shared.u16 %0,[%1];" : "=r"(v) : "r"(a) : "memory"); return v; }
DI uint2 lds64(uint32_t a) { uint2 v; asm volatile("ld.shared.v2.u32 {%0,%1},[%2];" : "=r"(v.x), "=r"(v.y) : "r"(a) : "memory"); return v; }
DI uint4 lds128(uint32_t a) { uint4 v; asm volatile("ld.shared.v4.u32 {%0,%1,%2,%3},[%4];" : "=r"(v.x), "=r"(v.y), "=r"(v.z), "=r"(v.w) : "r"(a) : "memory"); return v; }
DI void sts16(uint32_t a, uint32_t v) { asm volatile("st.shared.u16 [%0],%1;" ::"r"(a), "r"(v) : "memory"); }
DI void sts32(uint32_t a, uint32_t v) { asm volatile("st.shared.u32 [%0],%1;" ::"r"(a), "r"(v) : "memory"); }
DI void sts64(uint32_t a, uint32_t x, uint32_t y) { asm volatile("st.shared.v2.u32 [%0],{%1,%2};" ::"r"(a), "r"(x), "r"(y) : "memory"); }
DI void sts128(uint32_t a, uint32_t x, uint32_t y, uint32_t z, uint32_t w) { asm volatile("st.shared.v4.u32 [%0],{%1,%2,%3,%4};" ::"r"(a), "r"(x), "r"(y), "r"(z), "r"(w) : "memory"); }
DI uint4 ldsm4(uint32_t a) { uint4 v; asm volatile("ldmatrix.sync.aligned.m8n8.x4.shared.b16 {%0,%1,%2,%3},[%4];" : "=r"(v.x), "=r"(v.y), "=r"(v.z), "=r"(v.w) : "r"(a) : "memory"); return v; }
DI uint4 ldsm4t(uint32_t a) { uint4 v; asm volatile("ldmatrix.sync.aligned.m8n8.x4.trans.shared.b16 {%0,%1,%2,%3},[%4];" : "=r"(v.x), "=r"(v.y), "=r"(v.z), "=r"(v.w) : "r"(a) : "memory"); return v; }
DI void stsm4(uint32_t a, uint32_t x, uint32_t y, uint32_t z, uint32_t w) { asm volatile("stmatrix.sync.aligned.m8n8.x4.shared.b16 [%0],{%1,%2,%3,%4};" ::"r"(a), "r"(x), "r"(y), "r"(z), "r"(w) : "memory"); }
DI void stsm4t(uint32_t a, uint32_t x, uint32_t y, uint32_t z, uint32_t w) { asm volatile("stmatrix.sync.aligned.m8n8.x4.trans.shared.b16 [%0],{%1,%2,%3,%4};" ::"r"(a), "r"(x), "r"(y), "r"(z), "r"(w) : "memory"); }
DI void mma_bf(float (&d)[4], uint32_t a0, uint32_t a1, uint32_t a2, uint32_t a3, uint32_t b0, uint32_t b1) {
    asm("mma.sync.aligned.m16n8k16.row.col.f32.bf16.bf16.f32 {%0,%1,%2,%3},{%4,%5,%6,%7},{%8,%9},{%0,%1,%2,%3};"
        : "+f"(d[0]), "+f"(d[1]), "+f"(d[2]), "+f"(d[3]) : "r"(a0), "r"(a1), "r"(a2), "r"(a3), "r"(b0), "r"(b1));
}
DI void mma_bf(float (&d)[4], const uint4& a, uint32_t b0, uint32_t b1) { mma_bf(d, a.x, a.y, a.z, a.w, b0, b1); }
typedef uint32_t h4[2];
DI void mma_h(h4& d, const uint4& a, uint32_t b0, uint32_t b1) {
    asm("mma.sync.aligned.m16n8k16.row.col.f16.f16.f16.f16 {%0,%1},{%2,%3,%4,%5},{%6,%7},{%0,%1};"
        : "+r"(d[0]), "+r"(d[1]) : "r"(a.x), "r"(a.y), "r"(a.z), "r"(a.w), "r"(b0), "r"(b1));
}
DI void mma_k8(h4& d, uint32_t a0, uint32_t a1, uint32_t b0) {
    asm("mma.sync.aligned.m16n8k8.row.col.f16.f16.f16.f16 {%0,%1},{%2,%3},{%4},{%0,%1};" : "+r"(d[0]), "+r"(d[1]) : "r"(a0), "r"(a1), "r"(b0));
}
DI void mma_cvt(float (&d)[4], const h4& a, uint32_t b) {
    asm("mma.sync.aligned.m16n8k8.row.col.f32.f16.f16.f32 {%0,%1,%2,%3},{%4,%5},{%6},{%7,%7,%7,%7};"
        : "=f"(d[0]), "=f"(d[1]), "=f"(d[2]), "=f"(d[3]) : "r"(a[0]), "r"(a[1]), "r"(b), "f"(0.f));
}
DI uint32_t pk_bf(float lo, float hi) { uint32_t r; asm("cvt.rn.bf16x2.f32 %0,%1,%2;" : "=r"(r) : "f"(hi), "f"(lo)); return r; }
DI uint32_t pk_h(float lo, float hi) { uint32_t r; asm("cvt.rn.f16x2.f32 %0,%1,%2;" : "=r"(r) : "f"(hi), "f"(lo)); return r; }
DI float bf_lo(uint32_t v) { return __uint_as_float(v << 16); }
DI float bf_hi(uint32_t v) { return __uint_as_float(v & 0xffff0000u); }
DI float bfr(float x) { return bf_lo(pk_bf(x, 0.f)); }
DI uint32_t hadd(uint32_t a, uint32_t b) { uint32_t r; asm("add.rn.f16x2 %0,%1,%2;" : "=r"(r) : "r"(a), "r"(b)); return r; }
DI uint32_t hsub(uint32_t a, uint32_t b) { uint32_t r; asm volatile("sub.rn.f16x2 %0,%1,%2;" : "=r"(r) : "r"(a), "r"(b)); return r; }
DI uint32_t hscl(uint32_t a) { uint32_t r; asm("mul.rn.f16x2 %0,%1,%2;" : "=r"(r) : "r"(a), "r"(0x01000100)); return r; }
DI uint32_t bsub_lo(uint32_t x, uint32_t m) { uint32_t r; asm("{.reg .b16 l,h; .reg .b32 t; mov.b32 {l,h},%2; mov.b32 t,{l,l}; sub.rn.bf16x2 %0,%1,t;}" : "=r"(r) : "r"(x), "r"(m)); return r; }
DI uint32_t bmul(uint32_t a, uint32_t b) { uint32_t r; asm("mul.rn.bf16x2 %0,%1,%2;" : "=r"(r) : "r"(a), "r"(b)); return r; }
DI uint32_t bfma(uint32_t a, uint32_t b, uint32_t c) { uint32_t r; asm("fma.rn.bf16x2 %0,%1,%2,%3;" : "=r"(r) : "r"(a), "r"(b), "r"(c)); return r; }
DI float ex2(float x) { float r; asm("ex2.approx.ftz.f32 %0,%1;" : "=f"(r) : "f"(x)); return r; }
DI float rcp(float x) { float r; asm("rcp.approx.ftz.f32 %0,%1;" : "=f"(r) : "f"(x)); return r; }
DI float ftanh(float x) { float r; asm("tanh.approx.f32 %0,%1;" : "=f"(r) : "f"(x)); return r; }
DI float fsqrt(float x) { float r; asm("sqrt.approx.ftz.f32 %0,%1;" : "=f"(r) : "f"(x)); return r; }
constexpr float LOG2E = 1.4426950408889634f;
DI float sigm(float x) { return rcp(1.f + ex2(-LOG2E * x)); }
DI float silu(float x) { return x * sigm(x); }
struct cf { float r, i; };
DI cf cmul(cf a, cf b) { return {fmaf(a.r, b.r, -a.i * b.i), fmaf(a.r, b.i, a.i * b.r)}; }
DI float mul2(float a, float b) { float r; asm("{.reg .f32 t; mul.f32 t,%1,%2; mul.f32 %0,t,0f40000000;}" : "=f"(r) : "f"(a), "f"(b)); return r; }
DI cf csq(cf a) { return {fmaf(a.r, a.r, -a.i * a.i), mul2(a.r, a.i)}; }
DI cf csqc(cf a) { return {fmaf(a.r, a.r, -a.i * a.i), mul2(a.r, -a.i)}; }
DI cf cexp(float a2, float be, float p) { float m = ex2(a2 * p); float t = be * p; return {m * __cosf(t), m * __sinf(t)}; }

struct ch2 { uint32_t r, i; };
template <int V>
DI ch2 hmul(ch2 a, uint32_t fr, uint32_t fi) {
    ch2 o;
    if (V) asm("{.reg .b32 t,u; mul.rn.f16x2 t,%3,%5; neg.f16x2 t,t; mul.rn.f16x2 u,%2,%5; fma.rn.f16x2 %0,%2,%4,t; fma.rn.f16x2 %1,%3,%4,u;}"
               : "=&r"(o.r), "=r"(o.i) : "r"(a.r), "r"(a.i), "r"(fr), "r"(fi));
    else asm("{.reg .b32 t,u,n; mul.rn.f16x2 t,%2,%4; mul.rn.f16x2 u,%3,%4; neg.f16x2 n,%3; fma.rn.f16x2 %0,n,%5,t; fma.rn.f16x2 %1,%2,%5,u;}"
             : "=&r"(o.r), "=r"(o.i) : "r"(a.r), "r"(a.i), "r"(fr), "r"(fi));
    return o;
}
DI ch2 hmul(ch2 a, uint32_t f) {
    ch2 o;
    asm("{.reg .b32 t,u,x,y; .reg .b16 l,h; mov.b32 {l,h},%4; mov.b32 x,{l,l}; mov.b32 y,{h,h};\n"
        "mul.rn.f16x2 t,%3,y; neg.f16x2 t,t; fma.rn.f16x2 %0,%2,x,t; mul.rn.f16x2 u,%3,x; fma.rn.f16x2 %1,%2,y,u;}"
        : "=&r"(o.r), "=r"(o.i) : "r"(a.r), "r"(a.i), "r"(f));
    return o;
}
DI uint32_t pk_h(cf f) { return pk_h(f.r, f.i); }
DI void sts_ch2(uint32_t a, ch2 x, ch2 y, ch2 z, ch2 w) { sts128(a, x.r, y.r, z.r, w.r); sts128(a + 512, x.i, y.i, z.i, w.i); }

#define TDUMP
#define TS(i)
#define TV(i, v)
#define T2S(i)

DI uint4 toep(uint32_t a, uint32_t Z) {
    uint4 r; r.x = lds32(a); r.y = lds32(a + 16); r.z = lds32(a - 16); r.w = r.x ^ Z;
    return r;
}
DI void sched_fence(uint32_t Z) { if (FSB == 2) { asm volatile("griddepcontrol.launch_dependents;" ::: "memory"); return; } asm volatile("{.reg .pred p; setp.ne.u32 p,%0,0; @p griddepcontrol.launch_dependents;}" ::"r"(Z) : "memory"); }
DI uint32_t copy(uint32_t v, uint32_t Z) { uint32_t r; asm volatile("xor.b32 %0,%1,%2;" : "=r"(r) : "r"(v), "r"(Z)); return r; }
DI void pin4(uint32_t& a, uint32_t& b, uint32_t& c, uint32_t& d, uint32_t Z) {
    asm volatile("{.reg .pred p; setp.ne.u32 p,%4,0; @p ld.shared.v4.u32 {%0,%1,%2,%3},[%4];}" : "+r"(a), "+r"(b), "+r"(c), "+r"(d) : "r"(Z) : "memory");
}

#define BFRAG(B, s) ((s) & 1) ? B[(s) >> 1].z : B[(s) >> 1].x, ((s) & 1) ? B[(s) >> 1].w : B[(s) >> 1].y
DI uint32_t comp(const uint4& v, int k) { return k == 0 ? v.x : k == 1 ? v.y : k == 2 ? v.z : v.w; }
template <bool FIRST>
DI void conv_half(h4 (&acc)[16], uint32_t aA, uint32_t aB, uint32_t aE, uint32_t bar, uint32_t Z) {
    constexpr int O = FIRST ? 0 : 8, NT = FIRST ? 5 : 4;
    uint4 A[4], S[2], B[4] = {};
    h4 P[4], m1[5] = {};
#pragma unroll
    for (int i = 0; i < 4; i++) A[i] = toep(aA + 7 * 32 + i * 256, Z);
    S[0].z = hsub(A[0].y, A[1].y); S[1].z = hsub(A[2].y, A[3].y);
    if (!FIRST || ORD)
#pragma unroll
        for (int k = 0; k < 2 * NT; k++) acc[O + (k | 1)][k & 1] = hsub(acc[O + (k | 1)][k & 1], acc[O + (k & ~1)][k & 1]);
    auto refill = [&](int k) { A[k].y = copy(A[k].z, Z); A[k].x = lds32(aA + 6 * 32 + k * 256); A[k].z = lds32(aA + 6 * 32 + k * 256 - 16); };
    auto diff = [&](int k) {
        A[2 * k].w = copy(A[2 * k].x, Z); A[2 * k + 1].w = copy(A[2 * k + 1].x, Z);
        S[k].y = copy(S[k].z, Z); S[k].z = hsub(A[2 * k].z, A[2 * k + 1].z); S[k].x = hsub(A[2 * k].x, A[2 * k + 1].w); S[k].w = hsub(A[2 * k].w, A[2 * k + 1].x);
    };
    auto pre = [&](int s) { P[s][0] = hsub(B[s].z, B[s].x); P[s][1] = hsub(B[s].w, B[s].y); };
    auto head = [&]() {
#pragma unroll
        for (int s = 0; s < 4; s++) {
            if (s) pre(s - 1);
            if (s == 2) diff(1);
            mma_h(acc[O + 2 * s], A[0], B[s].x, B[s].y); mma_h(m1[s], A[1], B[s].z, B[s].w);
            if (FM >> s & 1) sched_fence(Z);
        }
    };
    auto rest = [&](bool ld) {
        pre(3);
        if (ld) { refill(0); refill(1); }
#pragma unroll
        for (int s = 0; s + 1 < NT; s++) {
            mma_h(acc[O + 2 * s + 2], A[2], B[s].x, B[s].y); mma_h(m1[s + 1], A[3], B[s].z, B[s].w);
            if (ld) { if (FM >> (4 + s + !FIRST) & 1) sched_fence(Z); B[s] = ldsm4(aB - 6 * BS + s * 2 * TS8); }
        }
        if (ld && NT == 4) B[3] = ldsm4(aB - 6 * BS + 6 * TS8);
        if (ld) { refill(2); refill(3); }
#pragma unroll
        for (int s = 0; s < 4; s++) mma_h(acc[O + 2 * ((s + !FIRST) & 3) + 1], S[0], P[(s + !FIRST) & 3][0], P[(s + !FIRST) & 3][1]);
        if (ld) { if (FM >> 8 & 1) sched_fence(Z); diff(0); }
        if (FIRST) mma_h(acc[9], S[1], P[3][0], P[3][1]);
#pragma unroll
        for (int s = 0; s < 3; s++) mma_h(acc[O + 2 * s + 3], S[1], P[s][0], P[s][1]);
        if (ld && (FM >> 9 & 1)) sched_fence(Z);
    };
    diff(0);
    if (FIRST && !ORD) { pin4(A[0].x, A[0].y, A[0].z, A[0].w, Z); pin4(A[1].x, A[1].y, A[1].z, A[1].w, Z); pin4(S[0].x, S[0].y, S[0].z, S[0].w, Z); }
    if (!ORD) mbar_wait(bar);
#pragma unroll
    for (int i = 0; i < 4; i++) B[i] = ldsm4(aB - 7 * BS + i * 2 * TS8);
    head();
#pragma unroll FUN
    for (int n = 0; n < 7; n++) {
        rest(true);
        head();
        aA -= 32; aB += BS;
    }
    if (ORD && FIRST) mbar_wait(bar + 8);
    const uint4 A32 = toep(aA + 224 + 1024, Z);
    uint4 A64, E[2];
    E[0] = ldsm4(aE);
    if (FIRST) { A64 = toep(aA + 224 + 1088, Z); E[1] = ldsm4(aE + 4 * TS8); }
    const uint4 Y = make_uint4(A32.y ^ Z, A32.y & Z, FIRST ? A64.y ^ Z : 0, FIRST ? A64.y & Z : 0);
    rest(false);
#pragma unroll
    for (int k = 0; k < 2 * NT; k++) acc[O + (k | 1)][k & 1] = hadd(hadd(acc[O + (k & ~1)][k & 1], m1[k >> 1][k & 1]), acc[O + (k | 1)][k & 1]);
#pragma unroll
    for (int k = 0; k < (FIRST ? 10 : 6); k++) {
        if (k < 8 || ORD) acc[O + 2 + (k & ~1)][k & 1] = hadd(acc[O + 2 + (k & ~1)][k & 1], m1[k >> 1][k & 1]);
        else acc[10][k & 1] = m1[4][k & 1];
    }
    if (FIRST) {
#pragma unroll
        for (int s = 7; s >= 0; s--) mma_h(acc[s + 8], A64, BFRAG(B, s));
#pragma unroll
        for (int s = 7; s >= 0; s--) mma_k8(acc[s + 8], Y.z, Y.w, comp(E[s >> 2], s & 3));
    }
#pragma unroll
    for (int s = 0; s < (FIRST ? 8 : 4); s++) mma_h(acc[O + s + 4], A32, BFRAG(B, s));
#pragma unroll
    for (int s = 0; s < (FIRST ? 8 : 4); s++) mma_k8(acc[O + s + 4], Y.x, Y.y, comp(E[s >> 2], s & 3));
}

__global__ void __cluster_dims__(2, 1, 1) __launch_bounds__(640, 1)
fused_kernel(const __grid_constant__ Params prm, const __grid_constant__ Maps maps) {
    const CUtensorMap &mg = maps.m[0], &md = maps.m[2], &mx = maps.m[3], &mo = maps.m[4];
    extern __shared__ __align__(1024) unsigned char smem_raw[];
    SCHED(X)
    const uint32_t tid = threadIdx.x;
    uint2 vA, vI, vR, vC;
    uint32_t ldt, Dsk;
    if (tid < 256) {
        const int e = blockIdx.x * 256 + tid;
        vA = ldg64(prm.logA + e); vI = ldg64(prm.Aim + e); vR = ldg64(prm.Cre + e); vC = ldg64(prm.Cim + e);
        ldt = prm.logdt[e >> 5]; Dsk = prm.Dsk[e >> 5];
    }
    const int t0 = __shfl_sync(~0u, now_ns() + (threadIdx.x >> 10), 0);
    uint32_t sb = (uint32_t)__cvta_generic_to_shared(smem_raw);
    if (SBC) sb = __shfl_sync(~0u, sb + (threadIdx.x >> 10), 0);
    const int b = blockIdx.x, rk = b & 1, q = b >> 1;
    const int w = __shfl_sync(~0u, tid >> 5, 0);
#define LANES const int lane = lane_id(), g = lane >> 2, c = lane & 3, mi = lane >> 3, r8 = lane & 7; (void)g; (void)c; (void)mi; (void)r8
    uint32_t pb;
    asm("mapa.shared::cluster.u32 %0,%1,%2;" : "=r"(pb) : "r"(sb), "r"(rk ^ 1));
    if (w < 17) asm volatile("barrier.cluster.arrive.relaxed.aligned;" ::: "memory");
    const uint32_t Z = prm.zero;
    if (w == 16) {
        asm volatile("{.reg .pred p; elect.sync _|p,0xffffffff; @p mbarrier.init.shared.b64 [%0],1; @p mbarrier.init.shared.b64 [%0+8],1; fence.mbarrier_init.release.cluster;\n"
                     "@p mbarrier.arrive.expect_tx.shared.b64 _,[%0],16384; @p mbarrier.arrive.expect_tx.shared.b64 _,[%0+8],16384;}" ::"r"(sb + B_ROW) : "memory");
        if (ROW0) spin(t0 + ROW0);
        bulk_e(sb + O_ROWS, prm.u + b * 1024, sb + B_ROW, 16384);
        TS(6);
    }

    if (w < 8) {
        LANES;
        const uint32_t pv = sb + O_PRIV + w * PRIV, tb = pv + P_TAB, rw = sb + O_RAW + w * 32;
        const uint32_t dd = g - 2 * c;
        uint32_t st = pv + lane * 16, cyP = pv + 528 + c * 1056 + mi * 4, Zr = Z;
        uint32_t a1 = tb + ((dd + 14) & 4) * (PB / 4) + ((dd + 14) >> 3) * 16 + ((dd + 14) & 3) * 4, t2 = tb + T2 + dd * 8;
        uint32_t aB = rw + r8 * BS + (mi >> 1) * TS8 + (mi & 1) * 16, ac0 = rw + lane * BS;
        uint32_t fa = pv + 16 + r8 * 16 + mi * 528, fb = fa + ((mi & 1) ? -528 : 512), fc = (mi < 2 ? fa : fb) + 4 * 528;
        uint32_t Id = (dd >> 1) ? 0 : 0x3c00 << (16 * (g & 1)), kt = pv + (mi * 8 + (r8 >> 1) + (r8 & 1) * 4) * 16;
        uint32_t w2 = tb + T2 + (lane & 1) * 320 + (lane >> 1) * 8, w3 = tb + T3 + lane * 4;
        sts64(rw - TS8 + g * BS + c * 8, 0, 0);
        sts128(tb + (mi & 1) * PB + (r8 < 2 ? r8 : r8 + 64) * 16, 0, 0, 0, 0);
        h4 kd[6] = {};
        uint32_t lA = pv + (mi >> 1) * 512 + (mi & 1) * 128 + r8 * 16, lB = pv + (2 + mi) * 512 + r8 * 16;
        uint32_t lC = pv + (6 + (mi & 1)) * 512 + (mi >> 1) * 128 + r8 * 16, lF = pv + 4096 + (mi & 1) * 64 + (mi >> 1) * 16;
        uint32_t sF = pv + 4096 + lane * 2, j0 = 0;
        pin4(a1, t2, aB, ac0, Z); pin4(fa, fb, fc, cyP, Z); pin4(st, Zr, Id, kt, Z); pin4(lA, lB, lC, lF, Z); pin4(sF, w2, w3, j0, Z);
        bar_sync(6, 288);
        asm volatile("setmaxnreg.inc.sync.aligned.u32 %0;" ::"n"(RM));
        const float dt = bfr(ex2(bf_lo(ldt + (lane & Z)) * LOG2E));
        uint32_t mx2 = __vmaxu2(__vmaxu2(vR.x & 0x7fff7fffu, vR.y & 0x7fff7fffu), __vmaxu2(vC.x & 0x7fff7fffu, vC.y & 0x7fff7fffu));
        const int ex = min(max(max((int)((__reduce_max_sync(~0u, max(mx2 >> 16, mx2 & 0xffffu)) >> 7) + (__float_as_uint(dt) >> 23)), (int)((Dsk >> 7) & 255) + 109), 140), 369);
        const float cs = dt * __uint_as_float((387 - ex) << 23), dl = -dt * LOG2E, ncs = __uint_as_float(__float_as_uint(cs) ^ 0x80000000u ^ Z);
        TS(w == 0 ? 0 : 63); T2S(0);
        auto gen = [&](uint32_t sel) {
            const float a2 = bfr(ex2(__uint_as_float(__byte_perm(vA.x, vA.y, sel) & 0xffff0000u) * LOG2E)) * dl;
            const float be = __uint_as_float(__byte_perm(vI.x, vI.y, sel) & 0xffff0000u) * dt;
            const cf wv = {__uint_as_float(__byte_perm(vR.x, vR.y, sel) & 0xffff0000u) * cs, __uint_as_float(__byte_perm(vC.x, vC.y, sel) & 0xffff0000u) * ncs};
            const cf y1 = cexp(a2, -be, 1.f), y2 = csq(y1), y4 = csq(y2), z8 = csqc(y4), z16 = csq(z8), z32 = csq(z16);
            const cf z64 = cexp(a2, be, 64.f);
            {
                const uint32_t f = pk_h(z64) ^ Z, f16 = pk_h(z16);
                const ch2 m0 = {pk_h(1.f, z32.r), pk_h(0.f, z32.i)}, m1 = hmul(m0, pk_h(z8));
                sts_ch2(st, m0, m1, hmul(m0, f16), hmul(m1, f16));
                sts16(sF, f); sts16(sF + 64, f >> 16);
            }
            if (KV & 4) sched_fence(Z);
            {
                const cf w4 = cmul(wv, y4), y256 = csqc(csq(z64)), y512 = csq(y256);
                const uint32_t f2 = pk_h(y2), f256 = pk_h(y256), f512 = pk_h(y512);
                const ch2 p0 = {pk_h(wv.r, w4.r), pk_h(wv.i, w4.i)};
                const ch2 p1 = hmul(p0, pk_h(y1)), p2 = hmul(p0, f2), p4 = hmul(p0, pk_h(y4));
                sts_ch2(st + 1024, p1, p2, hmul(p1, f2), p4);
                if (KV & 8) sched_fence(Z);
                const ch2 e1 = hmul(p4, f256);
                sts_ch2(st + 2048, hmul(p2, f256), e1, hmul(p4, f512), hmul(e1, f512));
                const ch2 g0 = {__byte_perm(p4.r, e1.r, 0x7632), __byte_perm(p4.i, e1.i, 0x7632)}, s0 = hmul(g0, pk_h(csq(y512)));
                sts_ch2(st + 3072, s0, hmul(s0, f512), p0, g0);
            }
            __syncwarp();
        };
        auto mul = [&]() {
#pragma unroll
            for (int k2 = 0; k2 < 2; k2++) {
                const uint4 M = ldsm4t(lA + k2 * 256), F = ldsm4(lF + k2 * 32);
                uint4 B[3];
                B[0] = ldsm4t(lB + k2 * 256); B[1] = ldsm4t(lB + k2 * 256 + 128); B[2] = ldsm4t(lC + k2 * 256);
#pragma unroll
                for (int i = 1; i >= 0; i--) {
                    const uint32_t fr = i ? F.z : F.x, fi = i ? F.w : F.y;
                    const ch2 m0 = {i ? M.y ^ Z : (KV & 1) ? M.x ^ Z : M.x, i ? M.w ^ Z : (KV & 1) ? M.z ^ Z : M.z}, m1 = hmul<1>(m0, fr, fi), m2 = hmul<0>(m1, fr, fi), m3 = hmul<1>(m2, fr, fi);
                    const uint4 A0 = make_uint4(m0.r, m1.r, m0.i, m1.i), A1 = make_uint4(m2.r, m3.r, m2.i, m3.i);
                    if (KV & 2) sched_fence(Z);
                    mma_h(kd[0], A0, B[i].x, B[i].y); mma_h(kd[1], A0, B[i].z, B[i].w); mma_h(kd[2], A0, i ? B[2].z : B[2].x, i ? B[2].w : B[2].y);
                    mma_h(kd[3], A1, B[i].x, B[i].y); mma_h(kd[4], A1, B[i].z, B[i].w); mma_h(kd[5], A1, i ? B[2].z : B[2].x, i ? B[2].w : B[2].y);
                }
            }
            __syncwarp();
        };
        gen(0x1044);
#pragma unroll 1
        for (uint32_t sel = 0x3244; sel < 0x8000; sel += 0x2200) {
            mul();
            gen(sel);
        }
        mul();
        TS(w == 0 ? 59 : w == 4 ? 60 : 63); T2S(1);
        {
#pragma unroll
            for (int nt = 0; nt < 3; nt++) stsm4(kt + nt * 512, kd[nt][0], kd[nt][1], kd[nt + 3][0], kd[nt + 3][1]);
            __syncwarp();
            uint4 R0 = lds128(st), R1 = lds128(st + 512), R2 = lds128(st + 1024);
            R0.x = hscl(R0.x); R0.y = hscl(R0.y); R0.z = hscl(R0.z); R0.w = hscl(R0.w);
            R1.x = hscl(R1.x); R1.y = hscl(R1.y); R1.z = hscl(R1.z); R1.w = hscl(R1.w);
            R2.x = hscl(R2.x); R2.y = hscl(R2.y); R2.z = hadd(hscl(R2.z), pk_h(bf_lo(Dsk) * __uint_as_float((370 - ex) << 23), 0.f));
            const bool l31 = lane == 31, l2 = lane < 2;
            uint32_t nx = __shfl_down_sync(~0u, R0.x, 1);
            if (l31) nx = R0.w >> 16;
            const uint32_t pr = __shfl_sync(~0u, l31 ? R0.w : R1.y, lane - 1);
            const uint32_t sA = __shfl_sync(~0u, R1.z, lane - 2), sB = __shfl_sync(~0u, R1.w, lane - 2);
            const uint32_t s0 = __shfl_sync(~0u, R2.x, lane - 2), s1 = __shfl_sync(~0u, R2.y, lane - 2);
            sts128(st + P_TAB + 32, __byte_perm(R0.y, R0.x, 0x5410), __byte_perm(R0.z, R0.y, 0x5410), __byte_perm(R0.w, R0.z, 0x5410), __byte_perm(R0.x, R0.w, 0x5432));
            sts128(st + P_TAB + PB + 32, __byte_perm(R0.y, R0.x, 0x7632), __byte_perm(R0.z, R0.y, 0x7632), __byte_perm(R0.w, R0.z, 0x7632), __byte_perm(R0.w, nx, 0x3254));
            const uint32_t d1 = __byte_perm(R1.y, 0, 0x1010), d3 = __byte_perm(R1.y, 0, 0x3232);
            sts128(st + P_TAB + 544, __byte_perm(pr, R1.x, 0x3254), __byte_perm(R1.y, R1.x, 0x5410), d1, d1);
            sts128(st + P_TAB + PB + 544, __byte_perm(R1.x, R1.y, 0x5432), __byte_perm(R1.y, R1.x, 0x7632), d3, d3);
            uint32_t a = w2;
            const uint32_t pA = l2 ? 0 : sA, pB = l2 ? sA : sB, pT = l2 ? sB : 0;
            sts64(a, __byte_perm(R1.z, pA, 0x5410), __byte_perm(R1.z, pA, 0x7632));
            sts64(a + 128, __byte_perm(R1.w, pB, 0x5410), __byte_perm(R1.w, pB, 0x7632));
            if (lane < 16) sts64(a + 256, pT << 16, pT & 0xffff0000u);
            a = w3;
            const uint32_t p0 = __byte_perm(0, s0, l2 ? 0x5432 : 0x7654), p1 = __byte_perm(s0, s1, l2 ? 0x5432 : 0x7654);
            sts32(a, __byte_perm(R2.x, p0, 0x5410)); sts32(a + 128, __byte_perm(R2.x, p0, 0x7632));
            sts32(a + 256, __byte_perm(R2.y, p1, 0x5410)); sts32(a + 384, __byte_perm(R2.y, p1, 0x7632));
            if (lane == 0) sts64(st + P_TAB + PB + 24, R2.z & 0xffffu, __byte_perm(R0.x, R2.z, 0x5410));
            if (l31) {
                sts64(st + P_TAB + 35 * 16, d3, d3 << 16);
                sts128(st + P_TAB + 39 * 16, 0, R1.w >> 16, __byte_perm(R1.w, 0, 0x3232), R1.w & 0xffff0000u);
            }
        }
        __syncwarp();
        TS(w == 0 ? 1 : 63); T2S(9);
        h4 acc[16] = {};
        const uint32_t t3 = t2 + T3 - T2, fo = st + 16, sc = (ex - 115) * 0x800080;
        auto put_tiles = [&](int i0, int i1, int bar) {
#pragma unroll
            for (int i = i0; i < i1; i++) {
                float d[4], e[4];
                mma_cvt(d, acc[2 * i], Id);
                mma_cvt(e, acc[2 * i + 1], Id);
                stsm4t(aB + (2 * i - 1) * TS8, bmul(pk_bf(d[0], d[1]), sc), bmul(pk_bf(d[2], d[3]), sc), bmul(pk_bf(e[0], e[1]), sc), bmul(pk_bf(e[2], e[3]), sc));
            }
            __syncwarp();
            mbar_arrive_e(sb + B_Y + bar * 8);
        };
        auto filter = [&](int p) {
            const uint32_t ac = ac0 + p * 4 * TS8;
            const uint4 q2 = lds128(ac), q3 = lds128(ac + 16);
            const uint32_t cy = p ? lds32(cyP + 512) : 0;
            const uint2 q0 = lds64(ac - BS + 8);
            const uint4 q1 = lds128(ac - BS + 16);
            __syncwarp();
            if (!ORD || p == 2) put_tiles(2 * p, 2 * p + 2, p);
            sts32(cyP, cy);
            const uint32_t U[13] = {q0.x, q0.y, q1.x, q1.y, q1.z, q1.w, q2.x, q2.y, q2.z, q2.w, q3.x, q3.y, q3.z};
            uint32_t Q[13], Pp[12], P4[12], C3[12], C5[10];
#pragma unroll
            for (int k = 1; k < 13; k++) Q[k] = __byte_perm(U[k - 1], U[k], 0x5432);
#pragma unroll
            for (int k = 1; k < 12; k++) Pp[k] = hadd(U[k], Q[k]);
#pragma unroll
            for (int k = 2; k < 12; k++) P4[k] = hadd(Pp[k], Pp[k - 1]);
#pragma unroll
            for (int k = 3; k < 12; k++) C3[k] = hadd(Pp[k], Q[k + 1]);
#pragma unroll
            for (int k = 1; k < 10; k++) C5[k] = hadd(P4[k + 1], U[k - 1]);
            if (p < 2)
#pragma unroll
                for (int h = 0; h < 2; h++) {
                    const int k = 2 + 4 * h;
                    sts128(fo + (4 + h) * 528, hadd(P4[k], C3[k + 1]), hadd(P4[k + 1], C3[k + 2]), hadd(P4[k + 2], C3[k + 3]), hadd(P4[k + 3], C3[k + 4]));
                    sts128(fo + (6 + h) * 528, hadd(P4[k + 2], C5[k - 1]), hadd(P4[k + 3], C5[k]), hadd(P4[k + 4], C5[k + 1]), hadd(P4[k + 5], C5[k + 2]));
                }
            sts128(fo, C3[4], C3[5], C3[6], C3[7]); sts128(fo + 528, C3[8], C3[9], C3[10], C3[11]);
            sts128(fo + 2 * 528, C5[2], C5[3], C5[4], C5[5]); sts128(fo + 3 * 528, C5[6], C5[7], C5[8], C5[9]);
            __syncwarp();
        };
        uint2 T[5], U2[5], V[8];
        auto coarse = [&](int p, bool load) {
            if (load)
#pragma unroll
                for (int D = 0; D < 5; D++) if (p < 2 || D < 4) T[D] = lds64(t2 + D * 64);
#pragma unroll
            for (int gl = 0; gl < 4; gl++) {
                const uint4 A = ldsm4t(fa + gl * 128);
#pragma unroll
                for (int D = 0; D < 5; D++) if (4 * p + gl + D + 4 < 16) mma_h(acc[4 * p + gl + D + 4], A, T[D].x, T[D].y);
            }
            if (load) {
#pragma unroll
                for (int D = 0; D < 5; D++) if (p < 2 || D < 4) U2[D] = lds64(t2 + 320 + D * 64);
#pragma unroll
                for (int D = 0; D < 8 - 4 * p; D++) V[D] = lds64(t3 + D * 64);
            }
#pragma unroll
            for (int gl = 0; gl < 4; gl++) {
                const uint4 A = ldsm4t(fb + gl * 128);
#pragma unroll
                for (int D = 0; D < 5; D++) if (4 * p + gl + D + 4 < 16) mma_h(acc[4 * p + gl + D + 4], A, U2[D].x, U2[D].y);
                if (p < 2) {
                    const uint4 A3 = ldsm4t(fc + gl * 128);
#pragma unroll
                    for (int D = 7; D >= 0; D--) if (4 * p + gl + D + 8 < 16) mma_h(acc[4 * p + gl + D + 8], A3, V[D].x, V[D].y);
                }
            }
        };
        T2S(10);
        if (!ORD) conv_half<true>(acc, a1, aB, ac0 - BS + 16, sb + B_RAW, Zr);
        else mbar_wait(sb + B_RAW);
        T2S(11);
        filter(0);
        coarse(0, true);
        filter(1);
        coarse(1, false);
        T2S(12);
        if (ORD) {
            conv_half<true>(acc, a1, aB, ac0 - BS + 16, sb + B_RAW, Zr);
            __syncwarp();
            put_tiles(0, 2, 0);
            put_tiles(2, 4, 1);
        }
        T2S(22);
        conv_half<false>(acc, a1, aB + 8 * TS8, ac0 - BS + 16 + 8 * TS8, sb + B_RAW + 8, Zr);
        T2S(23);
        filter(2);
        coarse(2, !TKEEP);
        put_tiles(6, 7, 3);
        put_tiles(7, 8, 4);
        T2S(24);
        TS(w == 0 ? 3 : (w == 7 ? 4 : 63));
        TDUMP;
    } else if (w < 16) {
        LANES;
        const int hw = w - 8;
        if (RH < 96) asm volatile("setmaxnreg.dec.sync.aligned.u32 %0;" ::"n"(RH));
        if (RH > 96) asm volatile("setmaxnreg.inc.sync.aligned.u32 %0;" ::"n"(RH));
        uint32_t tag;
        asm volatile("ld.relaxed.gpu.global.u32 %0,[%1];" : "=r"(tag) : "l"(prm.S->epoch + b) : "memory");
        tag = ~tag << 31;
        {
            uint32_t W[16];
#pragma unroll
            for (int k = 0; k < 4; k++) {
                const uint4 v = ldg128(prm.wr + hw * 16 + (k ^ (g & 1)) * 4 + c);
                W[4 * k] = v.x; W[4 * k + 1] = v.y; W[4 * k + 2] = v.z; W[4 * k + 3] = v.w;
            }
#pragma unroll
            for (int k = 0; k < 16; k++) if (g & 2) W[k] = 0x3f803f80u;
            const bool dg = mi == c, od = g & 1;
            uint32_t ra = sb + O_ROWS + g * 2048 + hw * 256 + od * 64 + c * 16;
            uint32_t pa = sb + O_PST + ((dg ? 0 : 8 + 4 * (g & 2)) + 2 * c + od) * 48 + hw * 4;
            TS(hw == 4 ? 22 : 63);
            bar_sync(3, 288);
#pragma unroll 1
            for (int hf = 0; hf < 2; hf++) {
                float d[4] = {}, e[4] = {};
                mbar_wait(sb + B_ROW + hf * 8);
                TS(hw == 4 ? (hf ? 23 : 58) : 63);
#pragma unroll
                for (int k = 0; k < 4; k++) {
                    const uint4 x = lds128((ra ^ ((k & 1) << 6)) + (k >> 1) * 128);
                    mma_bf(d, x.x ^ Z, W[4 * k], x.y ^ Z, W[4 * k + 1], x.x, x.y);
                    mma_bf(e, x.z ^ Z, W[4 * k + 2], x.w ^ Z, W[4 * k + 3], x.z, x.w);
                }
#define PICK2(e) (dg ? (od ? e[1] : e[0]) : (od ? e[3] : e[2]))
                sts32(pa, __float_as_uint(PICK2(d) + PICK2(e)));
                TS(hf ? 63 : 8 + hw);
                bar_arrive(1 + 3 * hf, 288);
                ra += 16384; pa += 1152;
            }
        }
        const int n0 = hw + (hw & 4);
        const uint32_t tok = n0 * 16 + (lane & 2) * 32 + (lane & 1) * 8 + g, xo = O_XT + lane * 32 + ((rk ^ g) & 1) * 16;
        const uint32_t ta = sb + O_RAW + (n0 + (r8 & 4)) * BS + (mi ^ 1) * 64 + (r8 & 1) * 32 + (r8 & 2) * 8;
        const uint2* sp = prm.S->stats + (b & 3) * 2048 + tok;
        uint4 x[8];
        uint2 u[8];
        uint32_t G[32];
        float h[32];
        auto load = [&](int hf) {
            mbar_wait(sb + B_X + hf * 8);
#pragma unroll
            for (int i = 4 * hf; i < 4 * hf + 4; i++) x[i] = lds128(sb + xo + hw * 1024 + (i & 3) * 8192 + hf * (O_XB - O_XT));
        };
        auto poll = [&](int hf) {
            mbar_wait(sb + B_GO + hf * 8);
            TS(hw == 3 ? 16 + hf : 63);
            const uint2* v = u + 4 * hf;
            int it = 0;
#pragma unroll 1
            do {
#pragma unroll
                for (int i = 4 * hf; i < 4 * hf + 4; i++) u[i] = ldr64(sp + i * 256);
            } while (__any_sync(~0u, (int)(((v[0].x ^ tag) | (v[1].x ^ tag)) | ((v[2].x ^ tag) | (v[3].x ^ tag))) < 0) && ++it < 100000);
            TV(hw == 7 ? 61 + hf : 63, it);
            TS(hw == 3 ? (hf ? 25 : 18) : 63);
        };
        auto norm = [&](int i0) {
#pragma unroll
            for (int i = i0; i < i0 + 2; i++) {
                const float r = fabsf(__uint_as_float(u[i].x));
                float* v = h + 8 * (i & 3);
#pragma unroll
                for (int k = 0; k < 4; k++) {
                    const uint32_t e = bsub_lo(comp(x[i], k), u[i].y);
                    v[2 * k] = bf_lo(e) * r; v[2 * k + 1] = bf_hi(e) * r;
                }
                stsm4t(ta + i * 2 * TS8, pk_h(v[2], v[3]), pk_h(v[0], v[1]), pk_h(v[6], v[7]), pk_h(v[4], v[5]));
            }
            if (i0 & 2) { __syncwarp(); mbar_arrive_e(sb + B_RAW + (i0 & 4) * 2); }
        };
        auto gate = [&](int i0) {
            uint32_t* v = G + 4 * i0;
            const float* e = h + 8 * (i0 & 3);
#pragma unroll
            for (int k = 0; k < 8; k++) v[k] = pk_bf(fmaf(e[2 * k], ftanh(e[2 * k]), e[2 * k]), fmaf(e[2 * k + 1], ftanh(e[2 * k + 1]), e[2 * k + 1]));
            pin4(v[0], v[1], v[2], v[3], Z); pin4(v[4], v[5], v[6], v[7], Z);
        };
        load(0); poll(0); norm(0); norm(2);
        TS(32 + hw);
        sched_fence(Z);
        gate(0); gate(2);
        TS(hw == 0 ? 20 : 63);
        load(1);
        pin4(x[7].x, x[7].y, x[7].z, x[7].w, Z);
        mbar_arrive_e(sb + B_XR);
        poll(1);
        mbar_wait(sb + B_XR);
        norm(4); gate(4);
        sched_fence(Z);
        norm(6);
        TS(hw == 3 ? 19 : 63);
        gate(6);
        TS(hw == 0 ? 21 : 63);
        if (RH2 < RH) asm volatile("setmaxnreg.dec.sync.aligned.u32 %0;" ::"n"(RH2));
        mbar_wait(sb + B_SEL);
        mbar_wait(sb + B_SEL + 8);
        if (hw == 0) {
            mbar_arrive_peer_e(pb + B_XF);
            if (lane == 0) prm.S->epoch[b] = lds32(sb + O_SEL + 32);
        }
        const uint32_t r0 = lds32(sb + O_SEL) - tok, r1 = lds32(sb + O_SEL + 16) - tok;
        const uint32_t mine = ((r0 & 255) ? 0 : 128 << (r0 >> 8)) | ((r1 & 255) ? 0 : 128 << (r1 >> 8));
        const uint32_t skip = __reduce_or_sync(~0u, mine);
        const bool loc = (hw >> 2) == rk;
        const uint32_t oa = (loc ? sb : pb) + xo + (hw & 3) * 1024, ob = B_O + (hw & 3) * 40;
        if (!loc) mbar_wait(sb + B_XF);
#pragma unroll
        for (int p = 0; p < 5; p++) {
            const int i0 = p < 4 ? 2 * p : 7, i1 = p < 3 ? 2 * p + 2 : p + 4;
            if (loc) mbar_expect_e(sb + ob + p * 8, (i1 - i0) * 512);
            if (p == 3 && b < NFFN) mbar_wait(sb + B_HR);
            mbar_wait(sb + B_Y + p * 8);
            TS(hw == 1 ? 26 + p : 63);
#pragma unroll
            for (int i = i0; i < i1; i++) {
                const uint4 s = ldsm4t(ta + (2 * i - 1) * TS8);
                x[i] = make_uint4(bfma(s.y, G[4 * i], x[i].x), bfma(s.x, G[4 * i + 1], x[i].y), bfma(s.w, G[4 * i + 2], x[i].z), bfma(s.z, G[4 * i + 3], x[i].w));
            }
            if (loc) {
#pragma unroll
                for (int i = i0; i < i1; i++) sts128(oa + i * 4096, x[i].x, x[i].y, x[i].z, x[i].w);
                mbar_wait(sb + ob + p * 8);
                TS(p == 4 ? 120 + hw : 63);
                fence_async();
                __syncwarp();
#pragma unroll
                for (int i = i0; i < i1; i++) {
                    tma5d_st_e(sb + O_XT + (hw & 3) * 1024 + i * 4096, &mo, q * 16, 4 * i + 2 * rk + ((skip >> i) & 128), hw & 3);
                }
            } else {
#pragma unroll
                for (int i = i0; i < i1; i++) st_async(oa + i * 4096, x[i], pb + ob + p * 8);
            }
        }
        if (skip) {
#pragma unroll
            for (int i = 0; i < 8; i++)
                if ((skip & ~mine) >> (7 + i) & 1) prm.out[(tok + i * 256) * 128 + b] = x[i];
        }
        asm volatile("cp.async.bulk.commit_group; cp.async.bulk.wait_group.read 0;" ::: "memory");
        TS(40 + hw);
        TDUMP;
    } else {
        asm volatile("setmaxnreg.dec.sync.aligned.u32 %0;" ::"n"(480 - 2 * RM - 2 * RH));
        LANES;
        const int fw = w - 16;
        const CUtensorMap* m1 = &mg + rk;
        if (fw == 0) {
            bar_arrive(5, 128);
            spin(t0 + ROW1);
            bulk_e(sb + O_ROWS + 16384, prm.u + (128 + b) * 1024, sb + B_ROW + 8, 16384);
            bar_sync(7, 64);
            if (b < NFFN) {
#pragma unroll 1
                for (int i = 0; i < 12; i++) {
                    spin(t0 + W0 + ((b * WD) >> 7) + min(i, NPE) * WD);
                    if (i == 4) mbar_wait(sb + B_P1);
                    if (i == 10) mbar_wait(sb + B_XR);
                    tma3d_e(sb + (i < 8 ? O_RING + i * 8192 : O_RNG3 + ((i + 2) & 3) * 8192), m1, i * 64, q, sb + B_FULL + i * 8);
                }
            }
        } else {
            if (lane == 0) {
#pragma unroll
                for (int i = 0; i < 21; i++)
                    asm volatile("mbarrier.init.shared.b64 [%0],%1;" ::"r"(sb + B_FULL - 8 + 8 * fw + i * 24), "r"(i < 18 ? 1 : 8) : "memory");
            }
            __syncwarp();
            asm volatile("fence.mbarrier_init.release.cluster; barrier.cluster.arrive.relaxed.aligned;" ::: "memory");
            asm volatile("prefetch.tensormap [%0];" ::"l"(&md - 1 + fw));
            asm volatile("prefetch.tensormap [%0];" ::"l"(m1));
            bar_sync(5, 128);
            if (fw == 1) {
                bar_arrive(3, 288);
                bar_arrive(6, 288);
                bar_arrive(7, 64);
                mbar_expect_e(sb + B_H, 256);
                mbar_expect_e(sb + B_X, 32768);
                mbar_expect_e(sb + B_X + 8, 32768);
                asm volatile("barrier.cluster.wait.aligned;" ::: "memory");
#pragma unroll 1
                for (int i = 0; i < 8; i++) {
                    spin(t0 + (i < 4 ? GAT0 + i * GATD : GAT1 + (i & 3) * GATE));
                    tma5d_mc_e(sb + (i < 4 ? O_XT : O_XB) + (i & 3) * 8192 + rk * 4096, &mx, q * 16, i * 4 + rk * 2, sb + B_X + (i & 4) * 2);
                }
            }
        }
        if (fw == 2) {
            sts32(sb + O_ONE + lane * 4, 0x3f803f80u);
            __syncwarp();
            mbar_expect_e(sb + B_XS, 4096);
            spin(t0 + TGO0);
            mbar_arrive_e(sb + B_GO);
        }
        if (fw == 3) {
            uint32_t ep;
            asm volatile("ld.relaxed.gpu.global.u32 %0,[%1];" : "=r"(ep) : "l"(prm.S->epoch + b) : "memory");
            ep += 1;
            sts32(sb + O_SEL + 32, ep);
            float sw[4] = {0.f, 0.f, 0.f, 0.f};
#pragma unroll
            for (int k = 0; k < 4; k++) mma_bf(sw, ldg128(prm.wr + k * 32 + lane), 0x3f803f80u, 0x3f803f80u);
            float wsum = sw[0] + sw[2];
#pragma unroll
            for (int o = 4; o < 32; o <<= 1) wsum += __shfl_xor_sync(~0u, wsum, o);
            uint2* dst = prm.S->stats + c * 2048 + b * 8 + g;
            uint32_t pa = sb + O_PST + g * 48 + (lane & 1) * 16, ky = 0;
            const uint32_t id = (ep & 1) * 0x8000 + 2047 - (lane & 1) * 1024 - b * 8 - g;
#pragma unroll 1
            for (int hf = 0; hf < 2; hf++) {
                bar_sync(1 + 3 * hf, 288);
                float v[3];
#pragma unroll
                for (int k = 0; k < 3; k++) {
                    const uint4 t = lds128(pa + k * 384);
                    v[k] = (__uint_as_float(t.x) + __uint_as_float(t.y)) + (__uint_as_float(t.z) + __uint_as_float(t.w));
                    v[k] += __shfl_xor_sync(~0u, v[k], 1);
                }
                const float mean = v[2] * (1.f / 1024.f);
                const float var = fmaxf(fmaf(-mean, mean, v[0] * (1.f / 1024.f)), 0.f);
                const float rs = rcp(bfr(fsqrt(bfr(bfr(var) + 1e-5f))));
                const uint32_t mk = pk_bf(mean, fmaf(-bfr(mean), wsum, v[1]) * rs);
                str64(dst, __float_as_uint(0.5f * rs) | ep << 31, mk);
                if ((lane & 1) == hf) ky = ((mk ^ (((int)mk >> 31) | 0x80000000u)) & 0xffff0000u) | id;
                TS(hf ? 63 : 5);
                dst += 1024; pa += 1152;
            }
            const uint32_t k1 = __reduce_max_sync(~0u, ky), k2 = __reduce_max_sync(~0u, ky == k1 ? 0u : ky);
            str64(prm.S->keys + g * 128 + b, k1, k2);
            TS(48);
            mbar_arrive_e(sb + B_P1);
        }
        uint32_t wa[4];
#pragma unroll
        for (int i = 0; i < 4; i++) wa[i] = sb + O_RING + fw * 8192 + ((mi >> 1) * 8 + r8) * 128 + (((2 * i + (mi & 1)) ^ r8) << 4);
        uint32_t xs = sb + mi * 16 + ((r8 & 2) ? O_ONE : O_XSEL + fw * 128 + (r8 & 1) * 2064), xd = (r8 & 2) ? 0 : 512;
        uint32_t dst = ((rk * 32 + fw * 4 + c) * 112 + q) * 8 + g, hs = sb + O_HT + (r8 & 1) * 144 + mi * 16;
        pin4(wa[0], wa[1], wa[2], wa[3], Z); pin4(xs, xd, dst, hs, Z);
        mbar_wait(sb + B_P1);
        const uint32_t ep = lds32(sb + O_SEL + 32);
        if (fw >= 2) {
            const uint2* kp = prm.S->keys + ((b & 3) * 2 + (fw & 1)) * 128 + lane * 2;
            const uint32_t tag = ep << 15;
            mbar_wait(sb + B_RAW);
            spin(t0 + TTOP);
            uint4 k, l;
            int it = 0;
#pragma unroll 1
            do { k = ldr128(kp); l = ldr128(kp + 64); } while (__any_sync(~0u, (((k.x ^ tag) | (k.z ^ tag)) | ((l.x ^ tag) | (l.z ^ tag))) & 0x8000) && ++it < 100000);
            TV(fw == 2 ? 24 : 63, it);
            TS(fw == 2 ? 49 : 63);
            uint32_t ky = __reduce_max_sync(~0u, max(max(k.x, k.z), max(l.x, l.z)));
            if (fw & 1) ky = __reduce_max_sync(~0u, max(max(k.x == ky ? k.y : k.x, k.z == ky ? k.w : k.z), max(l.x == ky ? l.y : l.x, l.z == ky ? l.w : l.z)));
            const uint32_t tok = ~ky & 2047;
            if (b < NFFN) bulk_e(sb + O_XSEL + (fw & 1) * 2064, prm.u + tok * 128, sb + B_XS, 2048);
            sched_fence(Z);
            if (fw == 3) mbar_arrive_e(sb + B_GO + 8);
            uint2 rc;
#pragma unroll 1
            do rc = ldr64(prm.S->stats + (b & 3) * 2048 + tok); while (__any_sync(~0u, (int)(rc.x ^ tag << 16) < 0) && ++it < 100000);
            sts128(sb + O_SEL + (fw & 1) * 16, tok, pk_bf(0.f, sigm(bf_hi(ky ^ (~((int)ky >> 31) | 0x80000000u)))), rc.y << 16, __float_as_uint(2.f * fabsf(__uint_as_float(rc.x))));
            __syncwarp();
            mbar_arrive_e(sb + B_SEL + (fw & 1) * 8);
        }
        if (b < NFFN) {
            float h[4][4] = {};
            uint4 A[8], B[2];
            const bool c1 = c & 1, c2 = c & 2;
            const uint32_t s2 = O_RNG3 + ((fw ^ 2) - fw) * 8192, bf = sb + B_FULL + fw * 8;
#define SLOT(n) ((n) % 3 == 2 ? s2 : (n) % 3 * 32768)
            auto ldA = [&](int k, int n, int hf) { A[k] = ldsm4t(wa[k & 3] + SLOT(n) + hf * 4096 + (k >> 2) * 2048); };
            auto half = [&](const uint4& x, int n, int hf) {
                sched_fence(Z);
#pragma unroll
                for (int k = 0; k < 8; k++) {
                    mma_bf(h[k & 3], A[k], k < 4 ? x.x : x.z, k < 4 ? x.y : x.w);
                    if (n >= 0) ldA(k, n, hf);
                }
            };
            mbar_wait(bf);
#pragma unroll
            for (int k = 0; k < 8; k++) ldA(k, 0, 0);
            mbar_wait(sb + B_XS);
            TS(fw == 1 ? 50 : 63);
            B[0] = ldsm4(xs);
#pragma unroll
            for (int n = 0; n < 4; n++) {
                TS(64 + fw + 4 * n);
                B[1] = ldsm4(xs + 64);
                half(B[0], n, 1);
                xs += xd;
                if (n < 3) { mbar_wait(bf + 32 * n + 32); B[0] = ldsm4(xs); }
                half(B[1], n < 3 ? n + 1 : -1, 0);
                TS(96 + fw + 4 * n);
                if (n < 3) {
                    sched_fence(Z);
                    if (n >= PACE) spin(t0 + W0 + ((b * WD) >> 7) + (fw + 4 * n + 12 - LEAD) * WD);
                    tma3d_e(sb + O_RING + fw * 8192 + SLOT(n), n ? &md : m1, (n ? q : fw + 12) * 64, n ? rk * 8 + fw + 4 * n - 4 : q, bf + 32 * n + 96);
                }
            }
#pragma unroll
            for (int j = 0; j < 4; j += 2)
                sts128(sb + O_RING + fw * 8192 + j * 256 + lane * 16, __float_as_uint(c2 ? h[j + 1][0] : h[j][0]), __float_as_uint(c2 ? h[j + 1][1] : h[j][1]),
                       __float_as_uint(c2 ? h[j + 1][2] : h[j][2]), __float_as_uint(c2 ? h[j + 1][3] : h[j][3]));
            if (fw >= 2) {
                bar_arrive(2, 128);
            } else {
                const uint32_t pa = sb + O_RING + fw * 512 + (lane >> 1) * 32 + (lane & 1) * 8, ha = sb + O_HT + fw * 64 + c * 16 + g * 2;
                mbar_wait(sb + B_SEL);
                mbar_wait(sb + B_SEL + 8);
                mbar_wait(sb + B_XF);
                const uint2 n0 = lds64(sb + O_SEL + 8), n1 = lds64(sb + O_SEL + 24);
                bar_sync(2, 128);
                TS(fw == 0 ? 51 : 63);
                float t[3][4];
#pragma unroll
                for (int j = 0; j < 4; j++) {
                    const uint2 p = lds64(pa + j * 8192);
                    t[0][j] = __uint_as_float(p.x); t[1][j] = __uint_as_float(p.y); t[2][j] = __uint_as_float(lds32(pa + j * 8192 + 16));
                }
                const float cs = (t[2][0] + t[2][1]) + (t[2][2] + t[2][3]);
                uint32_t v = pk_bf(fmaf(-__uint_as_float(n0.x), cs, (t[0][0] + t[0][1]) + (t[0][2] + t[0][3])) * __uint_as_float(n0.y),
                                   fmaf(-__uint_as_float(n1.x), cs, (t[1][0] + t[1][1]) + (t[1][2] + t[1][3])) * __uint_as_float(n1.y));
                if (rk == 0) v = pk_bf(silu(bf_lo(v)), silu(bf_hi(v)));
                asm volatile("st.async.shared::cluster.mbarrier::complete_tx::bytes.b32 [%0],%1,[%2];" ::"r"(pb + O_HX + fw * 128 + lane * 4), "r"(v), "r"(pb + B_H) : "memory");
                mbar_wait(sb + B_H);
                v = bmul(v, lds32(sb + O_HX + fw * 128 + lane * 4));
                sts16(ha, v); sts16(ha + 144, v >> 16);
                __syncwarp();
                asm volatile("{.reg .pred p; elect.sync _|p,0xffffffff; @p mbarrier.arrive.shared.b64 _,[%0],4;}" ::"r"(sb + B_HR) : "memory");
            }
#pragma unroll
            for (int n = 4; n < 6; n++) {
                mbar_wait(bf + 32 * n);
                TS(64 + fw + 4 * n);
#pragma unroll
                for (int k = 0; k < 8; k++) ldA(k, n, 0);
                if (n == 4) {
                    mbar_wait(sb + B_HR);
                    TS(fw == 0 ? 52 : 63);
                    B[0] = ldsm4(hs); B[1] = ldsm4(hs + 64);
                }
#pragma unroll
                for (int k = 0; k < 16; k++) h[k >> 2][k & 3] = 0.f;
                half(B[0], n, 1);
                half(B[1], -1, 0);
#define PICK(k) __float_as_uint(c2 ? (c1 ? h[3][k] : h[2][k]) : (c1 ? h[1][k] : h[0][k]))
                uint2* yo = prm.S->yp + dst + (n - 4) * 16 * 112 * 8;
                str64(yo, (PICK(0) & ~1u) | (ep & 1), PICK(1)); str64(yo + 448, (PICK(2) & ~1u) | (ep & 1), PICK(3));
                TS(96 + fw + 4 * n);
            }
            TS(fw == 0 ? 63 : 52 + fw);
        }
        if (!NOFIX && fw == 0) {
            mbar_wait(sb + B_SEL);
            mbar_wait(sb + B_SEL + 8);
            const uint4 sel = lds128(sb + O_SEL + (lane & 8) * 2);
            const uint32_t ch = 2 * c + (g & 1), go = sel.x * 1024 + b * 8 + ch;
            uint32_t xv;
            uint32_t sa = sb + O_RAW - TS8 + (sel.x >> 4) * BS + ch * 32 + (sel.x & 15) * 2;
            uint32_t ba = __reduce_max_sync(~0u, sel.x >> 8);
            ba = sb + B_Y + (ba == 7 ? 4 : ba >> 1) * 8;
            asm volatile("ld.global.nc.u16 %0,[%1];" : "=r"(xv) : "l"((const uint16_t*)prm.u + go) : "memory");
            xv <<= 16;
            uint32_t j0 = 0, xn = __float_as_uint(bfr(bfr(__uint_as_float(xv) - __uint_as_float(sel.z)) * __uint_as_float(sel.w)));
            pin4(xv, xn, sa, j0, Z);
            const uint4* yp = (const uint4*)prm.S->yp + b * 224 + lane;
            spin(t0 + TFIX);
            uint4 v[7];
            int it = 0;
            uint32_t bad, sv;
#pragma unroll 1
            do {
#pragma unroll
                for (int j = 0; j < 7; j++) v[j] = ldr128(yp + j * 32);
                mbar_wait(ba);
                sv = lds16(sa);
                bad = 0;
#pragma unroll
                for (int j = 0; j < 7; j++) asm volatile("{.reg .b32 t; lop3.b32 t,%1,%2,%3,0x7e; or.b32 %0,%0,t;}" : "+r"(bad) : "r"(v[j].x), "r"(ep), "r"(v[j].z));
            } while (__any_sync(~0u, bad & 1) && ++it < 100000);
            TV(57, it);
            float y[4];
#pragma unroll
            for (int k = 0; k < 4; k++)
                y[k] = ((__uint_as_float(comp(v[0], k)) + __uint_as_float(comp(v[1], k))) + (__uint_as_float(comp(v[2], k)) + __uint_as_float(comp(v[3], k)))) +
                       ((__uint_as_float(comp(v[4], k)) + __uint_as_float(comp(v[5], k))) + __uint_as_float(comp(v[6], k)));
            const bool b2 = lane & 4, b3 = lane & 8;
            const float y0 = (b2 ? y[2] : y[0]) + __shfl_xor_sync(~0u, b2 ? y[0] : y[2], 4), y1 = (b2 ? y[3] : y[1]) + __shfl_xor_sync(~0u, b2 ? y[1] : y[3], 4);
            float t = (b3 ? y1 : y0) + __shfl_xor_sync(~0u, b3 ? y0 : y1, 8);
            t += __shfl_xor_sync(~0u, t, 16);
            const float gt = bfr(silu(bfr(__uint_as_float(xn) + bfr(bfr(t) * __uint_as_float(sel.y)))));
            TS(56);
            ((uint16_t*)prm.out)[go] = pk_bf(fmaf(bf_lo(sv), gt, __uint_as_float(xv)), 0.f);
            TS(7);
        }
        TDUMP;
    }
}

typedef CUresult (*EncFn)(CUtensorMap*, CUtensorMapDataType, cuuint32_t, void*, const cuuint64_t*, const cuuint64_t*,
                          const cuuint32_t*, const cuuint32_t*, CUtensorMapInterleave, CUtensorMapSwizzle,
                          CUtensorMapL2promotion, CUtensorMapFloatOOBfill);

void make_map(EncFn f, CUtensorMap* m, const void* p, int rank, const cuuint64_t* gd, const cuuint64_t* gs,
              const cuuint32_t* bd, CUtensorMapSwizzle sw) {
    const cuuint32_t es[5] = {1, 1, 1, 1, 1};
    f(m, CU_TENSOR_MAP_DATA_TYPE_BFLOAT16, rank, const_cast<void*>(p), gd, gs, bd, es, CU_TENSOR_MAP_INTERLEAVE_NONE, sw,
      CU_TENSOR_MAP_L2_PROMOTION_NONE, CU_TENSOR_MAP_FLOAT_OOB_FILL_NONE);
}

}

extern "C" void kernel_launch(void* const* d_in, const int* in_sizes, int n_in, void* d_out, int out_size) {
    (void)in_sizes; (void)n_in; (void)out_size;
    void* fp = nullptr;
    cudaDriverEntryPointQueryResult qr;
    cudaGetDriverEntryPoint("cuTensorMapEncodeTiled", &fp, cudaEnableDefault, &qr);
    EncFn enc = (EncFn)fp;
    Maps maps;
    CUtensorMap &mg = maps.m[0], &mu = maps.m[1], &md = maps.m[2], &mx = maps.m[3], &mo = maps.m[4];
    {
        const cuuint64_t gd[3] = {64, 1024, 56}, gs[2] = {7168, 128};
        const cuuint32_t bd[3] = {64, 64, 1};
        make_map(enc, &mg, d_in[9], 3, gd, gs, bd, CU_TENSOR_MAP_SWIZZLE_128B);
        make_map(enc, &mu, d_in[10], 3, gd, gs, bd, CU_TENSOR_MAP_SWIZZLE_128B);
    }
    {
        const cuuint64_t gd[3] = {64, 3584, 16}, gs[2] = {2048, 128};
        const cuuint32_t bd[3] = {64, 64, 1};
        make_map(enc, &md, d_in[11], 3, gd, gs, bd, CU_TENSOR_MAP_SWIZZLE_128B);
    }
    {
        const cuuint64_t gd[5] = {1024, 2, 32, 8, 4}, gs[4] = {16384, 131072, 2048, 32768};
        const cuuint32_t bd[5] = {16, 2, 2, 8, 4}, bo[5] = {16, 2, 2, 8, 1};
        make_map(enc, &mx, d_in[0], 5, gd, gs, bd, CU_TENSOR_MAP_SWIZZLE_32B);
        make_map(enc, &mo, d_out, 5, gd, gs, bo, CU_TENSOR_MAP_SWIZZLE_32B);
    }
    Params p;
    p.u = (const uint4*)d_in[0]; p.logA = (const uint2*)d_in[1]; p.Aim = (const uint2*)d_in[2];
    p.Cre = (const uint2*)d_in[3]; p.Cim = (const uint2*)d_in[4];
    p.logdt = (const uint16_t*)d_in[5]; p.Dsk = (const uint16_t*)d_in[6]; p.wr = (const uint4*)d_in[8];
    p.out = (uint4*)d_out;
    void* sp = nullptr;
    cudaGetSymbolAddress(&sp, g_scratch);
    p.S = (Scratch*)sp; p.zero = 0;
    cudaFuncSetAttribute(fused_kernel, cudaFuncAttributeMaxDynamicSharedMemorySize, SMEM_BYTES + 512);
    fused_kernel<<<128, 640, SMEM_BYTES + 512, cudaStreamPerThread>>>(p, maps);
}
```

```cpp
#include <cuda_runtime.h>
#include <cuda_bf16.h>
#include <cuda_fp16.h>
#include <cuda.h>
#include <stdint.h>

#define RM 112
#define RH 88
#define ORD 0
#define FSB 1
#define RH2 RH
#define RF2 (480 - 2 * RM - 2 * RH2)
#define KV 1
#define FUNROLL 7
#define TKEEP 0
#define FM 1023
#define SBC 1
#define LATE 1
#define KLAGV 0
#define NOFIX 0
#define NFFN 112
namespace {

constexpr int RING = 8, FUN = FUNROLL;
constexpr uint32_t BS = 272, TS8 = 8 * BS;
constexpr uint32_t O_RING = 0;
constexpr uint32_t O_XT   = RING * 8192;
constexpr uint32_t O_RAW  = O_XT + 32768 + TS8;
constexpr uint32_t O_XB   = O_RAW + 8 * TS8 + 128;
constexpr uint32_t O_HX   = O_RAW + 16 * TS8;
constexpr uint32_t O_HT   = O_HX + 256;
constexpr uint32_t O_RNG3 = 133 * 1024;
constexpr uint32_t O_PST  = O_RNG3 + 3 * 8192;
constexpr uint32_t O_PRIV = O_RNG3 + 32768;
constexpr uint32_t PRIV   = 7744;
constexpr uint32_t P_TAB  = 4224;
constexpr uint32_t O_XSEL = O_XT + 6 * 4096;
constexpr uint32_t O_ROWS = (RING - 4) * 8192;
constexpr uint32_t O_SEL  = O_PRIV + 8 * PRIV;
constexpr uint32_t O_ONE  = O_SEL + 64;
constexpr uint32_t O_BAR  = O_ONE + 128;
constexpr uint32_t B_ROW = O_BAR, B_FULL = B_ROW + 16, B_H = B_FULL + 8 * 24, B_SEL = B_H + 8, B_P1 = B_SEL + 16,
                   B_X = B_P1 + 8, B_GO = B_X + 16, B_XS = B_GO + 16, B_XF = B_XS + 8, B_O = B_XF + 8, B_Y = B_O + 160, B_RAW = B_Y + 40, B_HR = B_RAW + 16, B_XR = B_HR + 8;
constexpr uint32_t SMEM_BYTES = B_Y + 72;
static_assert(B_Y - B_FULL == 18 * 24 && O_XB % 256 == 0 && O_HT + 288 <= O_RNG3 && O_XB + 32768 <= O_RNG3 + 16384, "layout");
static_assert(SMEM_BYTES + 512 <= 232448, "smem");
constexpr int PB = 1216, T2 = 2368, T3 = T2 + 640;

#define SCHED(X) X(0, ROW0, 330) X(1, ROW1, 1020) X(2, NPE, 11) X(3, GAT0, 900) X(4, GAT1, 2200) X(5, GATD, 60) X(6, TGO0, 2850) \
    X(7, TTOP, 4000) X(8, W0, 1750) X(9, WD, 280) X(10, LEAD, 1) X(11, GATE, 500) X(13, TFIX, 10020) X(14, PACE, 0) X(15, KLAG, KLAGV)
#define X(i, n, v) constexpr int n = v;

struct Scratch {
    uint2 stats[4 * 2048];
    uint2 keys[8 * 128];
    uint2 yp[128 * 56 * 8];
    unsigned epoch[128];
    int ts[128 * 128];
};
__device__ Scratch g_scratch;

struct Maps { CUtensorMap m[5]; };
struct Params {
    const uint4* u; const uint2* logA; const uint2* Aim; const uint2* Cre; const uint2* Cim;
    const uint16_t* logdt; const uint16_t* Dsk; const uint4* wr;
    uint4* out; Scratch* S; uint32_t zero;
};

#define DI __device__ __forceinline__
DI int lane_id() { int l; asm volatile("mov.u32 %0,%%laneid;" : "=r"(l)); __builtin_assume(l >= 0 && l < 32); return l; }
DI int now_ns() { int c; asm volatile("mov.u32 %0,%%globaltimer_lo;" : "=r"(c)::"memory"); return c; }
DI void spin(int t) {
    asm volatile("{.reg .pred p; .reg .s32 c; L: mov.u32 c,%%globaltimer_lo; sub.s32 c,c,%0; setp.lt.s32 p,c,0; @p nanosleep.u32 32; @p bra.uni L;}" ::"r"(t) : "memory");
}
DI void mbar_arrive_e(uint32_t b) { asm volatile("{.reg .pred p; elect.sync _|p,0xffffffff; @p mbarrier.arrive.shared.b64 _,[%0];}" ::"r"(b) : "memory"); }
DI void mbar_expect_e(uint32_t b, int tx) { asm volatile("{.reg .pred p; elect.sync _|p,0xffffffff; @p mbarrier.arrive.expect_tx.shared.b64 _,[%0],%1;}" ::"r"(b), "r"(tx) : "memory"); }
DI void mbar_wait(uint32_t b) {
    asm volatile("{.reg .pred p; W: mbarrier.try_wait.parity.shared.b64 p,[%0],0; @!p bra.uni W; }" ::"r"(b) : "memory");
}
DI void bulk_e(uint32_t dst, const void* src, uint32_t bar, int bytes) {
    asm volatile("{.reg .pred p; elect.sync _|p,0xffffffff; @p cp.async.bulk.shared::cluster.global.mbarrier::complete_tx::bytes [%0],[%1],%3,[%2];}" ::"r"(dst), "l"(src), "r"(bar), "r"(bytes) : "memory");
}
DI void tma3d_e(uint32_t dst, const CUtensorMap* m, int c1, int c2, uint32_t bar) {
    asm volatile("{.reg .pred p; elect.sync _|p,0xffffffff; @p mbarrier.arrive.expect_tx.shared.b64 _,[%2],8192;\n"
                 "@p cp.async.bulk.tensor.3d.shared::cluster.global.mbarrier::complete_tx::bytes [%0],[%1,{0,%3,%4}],[%2];}" ::"r"(dst), "l"(m), "r"(bar), "r"(c1), "r"(c2) : "memory");
}
DI void tma5d_mc_e(uint32_t dst, const CUtensorMap* m, int c0, int c2, uint32_t bar) {
    asm volatile("{.reg .pred p; elect.sync _|p,0xffffffff;\n"
                 "@p cp.async.bulk.tensor.5d.shared::cluster.global.mbarrier::complete_tx::bytes.multicast::cluster [%0],[%1,{%3,0,%4,0,0}],[%2],%5;}"
                 ::"r"(dst), "l"(m), "r"(bar), "r"(c0), "r"(c2), "h"((uint16_t)3) : "memory");
}
DI void tma5d_st_e(uint32_t src, const CUtensorMap* m, int c0, int c2, int c4) {
    asm volatile("{.reg .pred p; elect.sync _|p,0xffffffff; @p cp.async.bulk.tensor.5d.global.shared::cta.bulk_group [%1,{%2,0,%3,0,%4}],[%0];}" ::"r"(src), "l"(m), "r"(c0), "r"(c2), "r"(c4) : "memory");
}
DI void mbar_arrive_peer_e(uint32_t b) { asm volatile("{.reg .pred p; elect.sync _|p,0xffffffff; @p mbarrier.arrive.relaxed.cluster.shared::cluster.b64 _,[%0];}" ::"r"(b) : "memory"); }
DI void st_async(uint32_t dst, const uint4& v, uint32_t bar) {
    asm volatile("st.async.shared::cluster.mbarrier::complete_tx::bytes.v4.b32 [%0],{%1,%2,%3,%4},[%5];" ::"r"(dst), "r"(v.x), "r"(v.y), "r"(v.z), "r"(v.w), "r"(bar) : "memory");
}
DI void fence_async() { asm volatile("fence.proxy.async.shared::cta;" ::: "memory"); }
DI void bar_sync(int id, int n) { asm volatile("bar.sync %0,%1;" ::"r"(id), "r"(n) : "memory"); }
DI void bar_arrive(int id, int n) { asm volatile("bar.arrive %0,%1;" ::"r"(id), "r"(n) : "memory"); }
DI uint4 ldg128(const void* p) { uint4 v; asm volatile("ld.global.nc.v4.u32 {%0,%1,%2,%3},[%4];" : "=r"(v.x), "=r"(v.y), "=r"(v.z), "=r"(v.w) : "l"(p) : "memory"); return v; }
DI uint2 ldg64(const void* p) { uint2 v; asm volatile("ld.global.nc.v2.u32 {%0,%1},[%2];" : "=r"(v.x), "=r"(v.y) : "l"(p) : "memory"); return v; }
DI uint4 ldr128(const void* p) {
    uint4 v;
    asm volatile("{.reg .b128 t; .reg .b64 a,b; ld.relaxed.gpu.global.b128 t,[%4]; mov.b128 {a,b},t; mov.b64 {%0,%1},a; mov.b64 {%2,%3},b;}"
                 : "=r"(v.x), "=r"(v.y), "=r"(v.z), "=r"(v.w) : "l"(p) : "memory");
    return v;
}
DI uint2 ldr64(const void* p) { uint2 v; asm volatile("{.reg .b64 t; ld.relaxed.gpu.global.b64 t,[%2]; mov.b64 {%0,%1},t;}" : "=r"(v.x), "=r"(v.y) : "l"(p) : "memory"); return v; }
DI void str64(void* p, uint32_t x, uint32_t y) { asm volatile("{.reg .b64 t; mov.b64 t,{%1,%2}; st.relaxed.gpu.global.b64 [%0],t;}" ::"l"(p), "r"(x), "r"(y) : "memory"); }
DI uint32_t lds32(uint32_t a) { uint32_t v; asm volatile("ld.shared.u32 %0,[%1];" : "=r"(v) : "r"(a) : "memory"); return v; }
DI uint32_t lds16(uint32_t a) { uint32_t v; asm volatile("ld.shared.u16 %0,[%1];" : "=r"(v) : "r"(a) : "memory"); return v; }
DI uint2 lds64(uint32_t a) { uint2 v; asm volatile("ld.shared.v2.u32 {%0,%1},[%2];" : "=r"(v.x), "=r"(v.y) : "r"(a) : "memory"); return v; }
DI uint4 lds128(uint32_t a) { uint4 v; asm volatile("ld.shared.v4.u32 {%0,%1,%2,%3},[%4];" : "=r"(v.x), "=r"(v.y), "=r"(v.z), "=r"(v.w) : "r"(a) : "memory"); return v; }
DI void sts16(uint32_t a, uint32_t v) { asm volatile("st.shared.u16 [%0],%1;" ::"r"(a), "r"(v) : "memory"); }
DI void sts32(uint32_t a, uint32_t v) { asm volatile("st.shared.u32 [%0],%1;" ::"r"(a), "r"(v) : "memory"); }
DI void sts64(uint32_t a, uint32_t x, uint32_t y) { asm volatile("st.shared.v2.u32 [%0],{%1,%2};" ::"r"(a), "r"(x), "r"(y) : "memory"); }
DI void sts128(uint32_t a, uint32_t x, uint32_t y, uint32_t z, uint32_t w) { asm volatile("st.shared.v4.u32 [%0],{%1,%2,%3,%4};" ::"r"(a), "r"(x), "r"(y), "r"(z), "r"(w) : "memory"); }
DI uint4 ldsm4(uint32_t a) { uint4 v; asm volatile("ldmatrix.sync.aligned.m8n8.x4.shared.b16 {%0,%1,%2,%3},[%4];" : "=r"(v.x), "=r"(v.y), "=r"(v.z), "=r"(v.w) : "r"(a) : "memory"); return v; }
DI uint4 ldsm4t(uint32_t a) { uint4 v; asm volatile("ldmatrix.sync.aligned.m8n8.x4.trans.shared.b16 {%0,%1,%2,%3},[%4];" : "=r"(v.x), "=r"(v.y), "=r"(v.z), "=r"(v.w) : "r"(a) : "memory"); return v; }
DI void stsm4(uint32_t a, uint32_t x, uint32_t y, uint32_t z, uint32_t w) { asm volatile("stmatrix.sync.aligned.m8n8.x4.shared.b16 [%0],{%1,%2,%3,%4};" ::"r"(a), "r"(x), "r"(y), "r"(z), "r"(w) : "memory"); }
DI void stsm4t(uint32_t a, uint32_t x, uint32_t y, uint32_t z, uint32_t w) { asm volatile("stmatrix.sync.aligned.m8n8.x4.trans.shared.b16 [%0],{%1,%2,%3,%4};" ::"r"(a), "r"(x), "r"(y), "r"(z), "r"(w) : "memory"); }
DI void mma_bf(float (&d)[4], uint32_t a0, uint32_t a1, uint32_t a2, uint32_t a3, uint32_t b0, uint32_t b1) {
    asm("mma.sync.aligned.m16n8k16.row.col.f32.bf16.bf16.f32 {%0,%1,%2,%3},{%4,%5,%6,%7},{%8,%9},{%0,%1,%2,%3};"
        : "+f"(d[0]), "+f"(d[1]), "+f"(d[2]), "+f"(d[3]) : "r"(a0), "r"(a1), "r"(a2), "r"(a3), "r"(b0), "r"(b1));
}
DI void mma_bf(float (&d)[4], const uint4& a, uint32_t b0, uint32_t b1) { mma_bf(d, a.x, a.y, a.z, a.w, b0, b1); }
typedef uint32_t h4[2];
DI void mma_h(h4& d, const uint4& a, uint32_t b0, uint32_t b1) {
    asm("mma.sync.aligned.m16n8k16.row.col.f16.f16.f16.f16 {%0,%1},{%2,%3,%4,%5},{%6,%7},{%0,%1};"
        : "+r"(d[0]), "+r"(d[1]) : "r"(a.x), "r"(a.y), "r"(a.z), "r"(a.w), "r"(b0), "r"(b1));
}
DI void mma_k8(h4& d, uint32_t a0, uint32_t a1, uint32_t b0) {
    asm("mma.sync.aligned.m16n8k8.row.col.f16.f16.f16.f16 {%0,%1},{%2,%3},{%4},{%0,%1};" : "+r"(d[0]), "+r"(d[1]) : "r"(a0), "r"(a1), "r"(b0));
}
DI void mma_cvt(float (&d)[4], const h4& a, uint32_t b) {
    asm("mma.sync.aligned.m16n8k8.row.col.f32.f16.f16.f32 {%0,%1,%2,%3},{%4,%5},{%6},{%7,%7,%7,%7};"
        : "=f"(d[0]), "=f"(d[1]), "=f"(d[2]), "=f"(d[3]) : "r"(a[0]), "r"(a[1]), "r"(b), "f"(0.f));
}
DI uint32_t pk_bf(float lo, float hi) { uint32_t r; asm("cvt.rn.bf16x2.f32 %0,%1,%2;" : "=r"(r) : "f"(hi), "f"(lo)); return r; }
DI uint32_t pk_h(float lo, float hi) { uint32_t r; asm("cvt.rn.f16x2.f32 %0,%1,%2;" : "=r"(r) : "f"(hi), "f"(lo)); return r; }
DI float bf_lo(uint32_t v) { return __uint_as_float(v << 16); }
DI float bf_hi(uint32_t v) { return __uint_as_float(v & 0xffff0000u); }
DI float bfr(float x) { return bf_lo(pk_bf(x, 0.f)); }
DI uint32_t hadd(uint32_t a, uint32_t b) { uint32_t r; asm("add.rn.f16x2 %0,%1,%2;" : "=r"(r) : "r"(a), "r"(b)); return r; }
DI uint32_t hsub(uint32_t a, uint32_t b) { uint32_t r; asm volatile("sub.rn.f16x2 %0,%1,%2;" : "=r"(r) : "r"(a), "r"(b)); return r; }
DI uint32_t hscl(uint32_t a) { uint32_t r; asm("mul.rn.f16x2 %0,%1,%2;" : "=r"(r) : "r"(a), "r"(0x01000100)); return r; }
DI uint32_t bsub_lo(uint32_t x, uint32_t m) { uint32_t r; asm("{.reg .b16 l,h; .reg .b32 t; mov.b32 {l,h},%2; mov.b32 t,{l,l}; sub.rn.bf16x2 %0,%1,t;}" : "=r"(r) : "r"(x), "r"(m)); return r; }
DI uint32_t bmul(uint32_t a, uint32_t b) { uint32_t r; asm("mul.rn.bf16x2 %0,%1,%2;" : "=r"(r) : "r"(a), "r"(b)); return r; }
DI uint32_t bfma(uint32_t a, uint32_t b, uint32_t c) { uint32_t r; asm("fma.rn.bf16x2 %0,%1,%2,%3;" : "=r"(r) : "r"(a), "r"(b), "r"(c)); return r; }
DI float ex2(float x) { float r; asm("ex2.approx.ftz.f32 %0,%1;" : "=f"(r) : "f"(x)); return r; }
DI float rcp(float x) { float r; asm("rcp.approx.ftz.f32 %0,%1;" : "=f"(r) : "f"(x)); return r; }
DI float ftanh(float x) { float r; asm("tanh.approx.f32 %0,%1;" : "=f"(r) : "f"(x)); return r; }
DI float fsqrt(float x) { float r; asm("sqrt.approx.ftz.f32 %0,%1;" : "=f"(r) : "f"(x)); return r; }
constexpr float LOG2E = 1.4426950408889634f;
DI float sigm(float x) { return rcp(1.f + ex2(-LOG2E * x)); }
DI float silu(float x) { return x * sigm(x); }
struct cf { float r, i; };
DI cf cmul(cf a, cf b) { return {fmaf(a.r, b.r, -a.i * b.i), fmaf(a.r, b.i, a.i * b.r)}; }
DI float mul2(float a, float b) { float r; asm("{.reg .f32 t; mul.f32 t,%1,%2; mul.f32 %0,t,0f40000000;}" : "=f"(r) : "f"(a), "f"(b)); return r; }
DI cf csq(cf a) { return {fmaf(a.r, a.r, -a.i * a.i), mul2(a.r, a.i)}; }
DI cf csqc(cf a) { return {fmaf(a.r, a.r, -a.i * a.i), mul2(a.r, -a.i)}; }
DI cf cexp(float a2, float be, float p) { float m = ex2(a2 * p); float t = be * p; return {m * __cosf(t), m * __sinf(t)}; }

struct ch2 { uint32_t r, i; };
template <int V>
DI ch2 hmul(ch2 a, uint32_t fr, uint32_t fi) {
    ch2 o;
    if (V) asm("{.reg .b32 t,u; mul.rn.f16x2 t,%3,%5; neg.f16x2 t,t; mul.rn.f16x2 u,%2,%5; fma.rn.f16x2 %0,%2,%4,t; fma.rn.f16x2 %1,%3,%4,u;}"
               : "=&r"(o.r), "=r"(o.i) : "r"(a.r), "r"(a.i), "r"(fr), "r"(fi));
    else asm("{.reg .b32 t,u,n; mul.rn.f16x2 t,%2,%4; mul.rn.f16x2 u,%3,%4; neg.f16x2 n,%3; fma.rn.f16x2 %0,n,%5,t; fma.rn.f16x2 %1,%2,%5,u;}"
             : "=&r"(o.r), "=r"(o.i) : "r"(a.r), "r"(a.i), "r"(fr), "r"(fi));
    return o;
}
DI ch2 hmul(ch2 a, uint32_t f) {
    ch2 o;
    asm("{.reg .b32 t,u,x,y; .reg .b16 l,h; mov.b32 {l,h},%4; mov.b32 x,{l,l}; mov.b32 y,{h,h};\n"
        "mul.rn.f16x2 t,%3,y; neg.f16x2 t,t; fma.rn.f16x2 %0,%2,x,t; mul.rn.f16x2 u,%3,x; fma.rn.f16x2 %1,%2,y,u;}"
        : "=&r"(o.r), "=r"(o.i) : "r"(a.r), "r"(a.i), "r"(f));
    return o;
}
DI uint32_t pk_h(cf f) { return pk_h(f.r, f.i); }
DI void sts_ch2(uint32_t a, ch2 x, ch2 y, ch2 z, ch2 w) { sts128(a, x.r, y.r, z.r, w.r); sts128(a + 512, x.i, y.i, z.i, w.i); }

#define TDUMP
#define TS(i)
#define TV(i, v)
#define T2S(i)

DI uint4 toep(uint32_t a, uint32_t Z) {
    uint4 r; r.x = lds32(a); r.y = lds32(a + 16); r.z = lds32(a - 16); r.w = r.x ^ Z;
    return r;
}
DI void sched_fence(uint32_t Z) { if (FSB == 2) { asm volatile("griddepcontrol.launch_dependents;" ::: "memory"); return; } asm volatile("{.reg .pred p; setp.ne.u32 p,%0,0; @p griddepcontrol.launch_dependents;}" ::"r"(Z) : "memory"); }
DI uint32_t copy(uint32_t v, uint32_t Z) { uint32_t r; asm volatile("xor.b32 %0,%1,%2;" : "=r"(r) : "r"(v), "r"(Z)); return r; }
DI void pin4(uint32_t& a, uint32_t& b, uint32_t& c, uint32_t& d, uint32_t Z) {
    asm volatile("{.reg .pred p; setp.ne.u32 p,%4,0; @p ld.shared.v4.u32 {%0,%1,%2,%3},[%4];}" : "+r"(a), "+r"(b), "+r"(c), "+r"(d) : "r"(Z) : "memory");
}

#define BFRAG(B, s) ((s) & 1) ? B[(s) >> 1].z : B[(s) >> 1].x, ((s) & 1) ? B[(s) >> 1].w : B[(s) >> 1].y
DI uint32_t comp(const uint4& v, int k) { return k == 0 ? v.x : k == 1 ? v.y : k == 2 ? v.z : v.w; }
template <bool FIRST>
DI void conv_half(h4 (&acc)[16], uint32_t aA, uint32_t aB, uint32_t aE, uint32_t bar, uint32_t Z) {
    constexpr int O = FIRST ? 0 : 8, NT = FIRST ? 5 : 4;
    uint4 A[4], S[2], B[4] = {};
    h4 P[4], m1[5] = {};
#pragma unroll
    for (int i = 0; i < 4; i++) A[i] = toep(aA + 7 * 32 + i * 256, Z);
    S[0].z = hsub(A[0].y, A[1].y); S[1].z = hsub(A[2].y, A[3].y);
    if (!FIRST || ORD)
#pragma unroll
        for (int k = 0; k < 2 * NT; k++) acc[O + (k | 1)][k & 1] = hsub(acc[O + (k | 1)][k & 1], acc[O + (k & ~1)][k & 1]);
    auto refill = [&](int k) { A[k].y = copy(A[k].z, Z); A[k].x = lds32(aA + 6 * 32 + k * 256); A[k].z = lds32(aA + 6 * 32 + k * 256 - 16); };
    auto diff = [&](int k) {
        A[2 * k].w = copy(A[2 * k].x, Z); A[2 * k + 1].w = copy(A[2 * k + 1].x, Z);
        S[k].y = copy(S[k].z, Z); S[k].z = hsub(A[2 * k].z, A[2 * k + 1].z); S[k].x = hsub(A[2 * k].x, A[2 * k + 1].w); S[k].w = hsub(A[2 * k].w, A[2 * k + 1].x);
    };
    auto pre = [&](int s) { P[s][0] = hsub(B[s].z, B[s].x); P[s][1] = hsub(B[s].w, B[s].y); };
    auto head = [&]() {
#pragma unroll
        for (int s = 0; s < 4; s++) {
            if (s) pre(s - 1);
            if (s == 2) diff(1);
            mma_h(acc[O + 2 * s], A[0], B[s].x, B[s].y); mma_h(m1[s], A[1], B[s].z, B[s].w);
            if (FM >> s & 1) sched_fence(Z);
        }
    };
    auto rest = [&](bool ld) {
        pre(3);
        if (ld) { refill(0); refill(1); }
#pragma unroll
        for (int s = 0; s + 1 < NT; s++) {
            mma_h(acc[O + 2 * s + 2], A[2], B[s].x, B[s].y); mma_h(m1[s + 1], A[3], B[s].z, B[s].w);
            if (ld) { if (FM >> (4 + s + !FIRST) & 1) sched_fence(Z); B[s] = ldsm4(aB - 6 * BS + s * 2 * TS8); }
        }
        if (ld && NT == 4) B[3] = ldsm4(aB - 6 * BS + 6 * TS8);
        if (ld) { refill(2); refill(3); }
#pragma unroll
        for (int s = 0; s < 4; s++) mma_h(acc[O + 2 * ((s + !FIRST) & 3) + 1], S[0], P[(s + !FIRST) & 3][0], P[(s + !FIRST) & 3][1]);
        if (ld) { if (FM >> 8 & 1) sched_fence(Z); diff(0); }
        if (FIRST) mma_h(acc[9], S[1], P[3][0], P[3][1]);
#pragma unroll
        for (int s = 0; s < 3; s++) mma_h(acc[O + 2 * s + 3], S[1], P[s][0], P[s][1]);
        if (ld && (FM >> 9 & 1)) sched_fence(Z);
    };
    diff(0);
    if (FIRST && !ORD) { pin4(A[0].x, A[0].y, A[0].z, A[0].w, Z); pin4(A[1].x, A[1].y, A[1].z, A[1].w, Z); pin4(S[0].x, S[0].y, S[0].z, S[0].w, Z); }
    if (!ORD) mbar_wait(bar);
#pragma unroll
    for (int i = 0; i < 4; i++) B[i] = ldsm4(aB - 7 * BS + i * 2 * TS8);
    head();
#pragma unroll FUN
    for (int n = 0; n < 7; n++) {
        rest(true);
        head();
        aA -= 32; aB += BS;
    }
    if (ORD && FIRST) mbar_wait(bar + 8);
    const uint4 A32 = toep(aA + 224 + 1024, Z);
    uint4 A64, E[2];
    E[0] = ldsm4(aE);
    if (FIRST) { A64 = toep(aA + 224 + 1088, Z); E[1] = ldsm4(aE + 4 * TS8); }
    const uint4 Y = make_uint4(A32.y ^ Z, A32.y & Z, FIRST ? A64.y ^ Z : 0, FIRST ? A64.y & Z : 0);
    rest(false);
#pragma unroll
    for (int k = 0; k < 2 * NT; k++) acc[O + (k | 1)][k & 1] = hadd(hadd(acc[O + (k & ~1)][k & 1], m1[k >> 1][k & 1]), acc[O + (k | 1)][k & 1]);
#pragma unroll
    for (int k = 0; k < (FIRST ? 10 : 6); k++) {
        if (k < 8 || ORD) acc[O + 2 + (k & ~1)][k & 1] = hadd(acc[O + 2 + (k & ~1)][k & 1], m1[k >> 1][k & 1]);
        else acc[10][k & 1] = m1[4][k & 1];
    }
    if (FIRST) {
#pragma unroll
        for (int s = 7; s >= 0; s--) mma_h(acc[s + 8], A64, BFRAG(B, s));
#pragma unroll
        for (int s = 7; s >= 0; s--) mma_k8(acc[s + 8], Y.z, Y.w, comp(E[s >> 2], s & 3));
    }
#pragma unroll
    for (int s = 0; s < (FIRST ? 8 : 4); s++) mma_h(acc[O + s + 4], A32, BFRAG(B, s));
#pragma unroll
    for (int s = 0; s < (FIRST ? 8 : 4); s++) mma_k8(acc[O + s + 4], Y.x, Y.y, comp(E[s >> 2], s & 3));
}

__global__ void __cluster_dims__(2, 1, 1) __launch_bounds__(640, 1)
fused_kernel(const __grid_constant__ Params prm, const __grid_constant__ Maps maps) {
    const CUtensorMap &mg = maps.m[0], &md = maps.m[2], &mx = maps.m[3], &mo = maps.m[4];
    extern __shared__ __align__(1024) unsigned char smem_raw[];
    SCHED(X)
    const uint32_t tid = threadIdx.x;
    uint2 vA, vI, vR, vC;
    uint32_t ldt, Dsk;
    if (tid < 256) {
        const int e = blockIdx.x * 256 + tid;
        asm volatile("ld.global.nc.u16 %0,[%1];" : "=r"(ldt) : "l"(prm.logdt + (e >> 5)) : "memory");
        asm volatile("ld.global.nc.u16 %0,[%1];" : "=r"(Dsk) : "l"(prm.Dsk + (e >> 5)) : "memory");
        vA = ldg64(prm.logA + e); vI = ldg64(prm.Aim + e); vR = ldg64(prm.Cre + e); vC = ldg64(prm.Cim + e);
    }
    const int t0 = __shfl_sync(~0u, now_ns() + (threadIdx.x >> 10), 0);
    uint32_t sb = (uint32_t)__cvta_generic_to_shared(smem_raw);
    if (SBC) sb = __shfl_sync(~0u, sb + (threadIdx.x >> 10), 0);
    const int b = blockIdx.x, rk = b & 1, q = b >> 1;
    const int w = __shfl_sync(~0u, tid >> 5, 0);
#define LANES const int lane = lane_id(), g = lane >> 2, c = lane & 3, mi = lane >> 3, r8 = lane & 7; (void)g; (void)c; (void)mi; (void)r8
    uint32_t pb;
    asm("mapa.shared::cluster.u32 %0,%1,%2;" : "=r"(pb) : "r"(sb), "r"(rk ^ 1));
    if (w < 17) asm volatile("barrier.cluster.arrive.relaxed.aligned;" ::: "memory");
    const uint32_t Z = prm.zero;

    if (w < 8) {
        LANES;
        const uint32_t pv = sb + O_PRIV + w * PRIV, tb = pv + P_TAB, rw = sb + O_RAW + w * 32;
        const uint32_t dd = g - 2 * c;
        uint32_t st = pv + lane * 16, cyP = pv + 528 + c * 1056 + mi * 4, Zr = Z;
        uint32_t a1 = tb + ((dd + 14) & 4) * (PB / 4) + ((dd + 14) >> 3) * 16 + ((dd + 14) & 3) * 4, t2 = tb + T2 + dd * 8;
        uint32_t aB = rw + r8 * BS + (mi >> 1) * TS8 + (mi & 1) * 16, ac0 = rw + lane * BS;
        uint32_t fa = pv + 16 + r8 * 16 + mi * 528, fb = fa + ((mi & 1) ? -528 : 512), fc = (mi < 2 ? fa : fb) + 4 * 528;
        uint32_t Id = (dd >> 1) ? 0 : 0x3c00 << (16 * (g & 1)), kt = pv + (mi * 8 + (r8 >> 1) + (r8 & 1) * 4) * 16;
        uint32_t w2 = tb + T2 + (lane & 1) * 320 + (lane >> 1) * 8, w3 = tb + T3 + lane * 4;
        sts64(rw - TS8 + g * BS + c * 8, 0, 0);
        sts128(tb + (mi & 1) * PB + (r8 < 2 ? r8 : r8 + 64) * 16, 0, 0, 0, 0);
        h4 kd[6] = {};
        uint32_t lA = pv + (mi >> 1) * 512 + (mi & 1) * 128 + r8 * 16, lB = pv + (2 + mi) * 512 + r8 * 16;
        uint32_t lC = pv + (6 + (mi & 1)) * 512 + (mi >> 1) * 128 + r8 * 16, lF = pv + 4096 + (mi & 1) * 64 + (mi >> 1) * 16;
        uint32_t sF = pv + 4096 + lane * 2, j0 = 0;
        pin4(a1, t2, aB, ac0, Z); pin4(fa, fb, fc, cyP, Z); pin4(st, Zr, Id, kt, Z); pin4(lA, lB, lC, lF, Z); pin4(sF, w2, w3, j0, Z);
        sched_fence(Z);
        if (!LATE) asm volatile("setmaxnreg.inc.sync.aligned.u32 %0;" ::"n"(RM));
        const float dt = bfr(ex2(bf_lo(ldt + (lane & Z)) * LOG2E));
        uint32_t mx2 = __vmaxu2(__vmaxu2(vR.x & 0x7fff7fffu, vR.y & 0x7fff7fffu), __vmaxu2(vC.x & 0x7fff7fffu, vC.y & 0x7fff7fffu));
        const int ex = min(max(max((int)((__reduce_max_sync(~0u, max(mx2 >> 16, mx2 & 0xffffu)) >> 7) + (__float_as_uint(dt) >> 23)), (int)((Dsk >> 7) & 255) + 109), 140), 369);
        const float cs = dt * __uint_as_float((387 - ex) << 23), dl = -dt * LOG2E, ncs = __uint_as_float(__float_as_uint(cs) ^ 0x80000000u ^ Z);
        TS(88 + w); T2S(0);
        auto gen = [&](uint32_t sel) {
            const float a2 = bfr(ex2(__uint_as_float(__byte_perm(vA.x, vA.y, sel) & 0xffff0000u) * LOG2E)) * dl;
            const float be = __uint_as_float(__byte_perm(vI.x, vI.y, sel) & 0xffff0000u) * dt;
            const cf wv = {__uint_as_float(__byte_perm(vR.x, vR.y, sel) & 0xffff0000u) * cs, __uint_as_float(__byte_perm(vC.x, vC.y, sel) & 0xffff0000u) * ncs};
            const cf y1 = cexp(a2, -be, 1.f), y2 = csq(y1), y4 = csq(y2), z8 = csqc(y4), z16 = csq(z8), z32 = csq(z16);
            const cf z64 = cexp(a2, be, 64.f);
            {
                const uint32_t f = pk_h(z64) ^ Z, f16 = pk_h(z16);
                const ch2 m0 = {pk_h(1.f, z32.r), pk_h(0.f, z32.i)}, m1 = hmul(m0, pk_h(z8));
                sts_ch2(st, m0, m1, hmul(m0, f16), hmul(m1, f16));
                sts16(sF, f); sts16(sF + 64, f >> 16);
            }
            if (KV & 4) sched_fence(Z);
            {
                const cf w4 = cmul(wv, y4), y256 = csqc(csq(z64)), y512 = csq(y256);
                const uint32_t f2 = pk_h(y2), f256 = pk_h(y256), f512 = pk_h(y512);
                const ch2 p0 = {pk_h(wv.r, w4.r), pk_h(wv.i, w4.i)};
                const ch2 p1 = hmul(p0, pk_h(y1)), p2 = hmul(p0, f2), p4 = hmul(p0, pk_h(y4));
                sts_ch2(st + 1024, p1, p2, hmul(p1, f2), p4);
                if (KV & 8) sched_fence(Z);
                const ch2 e1 = hmul(p4, f256);
                sts_ch2(st + 2048, hmul(p2, f256), e1, hmul(p4, f512), hmul(e1, f512));
                const ch2 g0 = {__byte_perm(p4.r, e1.r, 0x7632), __byte_perm(p4.i, e1.i, 0x7632)}, s0 = hmul(g0, pk_h(csq(y512)));
                sts_ch2(st + 3072, s0, hmul(s0, f512), p0, g0);
            }
            __syncwarp();
        };
        auto mul = [&]() {
#pragma unroll
            for (int k2 = 0; k2 < 2; k2++) {
                const uint4 M = ldsm4t(lA + k2 * 256), F = ldsm4(lF + k2 * 32);
                uint4 B[3];
                B[0] = ldsm4t(lB + k2 * 256); B[1] = ldsm4t(lB + k2 * 256 + 128); B[2] = ldsm4t(lC + k2 * 256);
#pragma unroll
                for (int i = 1; i >= 0; i--) {
                    const uint32_t fr = i ? F.z : F.x, fi = i ? F.w : F.y;
                    const ch2 m0 = {i ? M.y ^ Z : (KV & 1) ? M.x ^ Z : M.x, i ? M.w ^ Z : (KV & 1) ? M.z ^ Z : M.z}, m1 = hmul<1>(m0, fr, fi), m2 = hmul<0>(m1, fr, fi), m3 = hmul<1>(m2, fr, fi);
                    const uint4 A0 = make_uint4(m0.r, m1.r, m0.i, m1.i), A1 = make_uint4(m2.r, m3.r, m2.i, m3.i);
                    if (KV & 2) sched_fence(Z);
                    mma_h(kd[0], A0, B[i].x, B[i].y); mma_h(kd[1], A0, B[i].z, B[i].w); mma_h(kd[2], A0, i ? B[2].z : B[2].x, i ? B[2].w : B[2].y);
                    mma_h(kd[3], A1, B[i].x, B[i].y); mma_h(kd[4], A1, B[i].z, B[i].w); mma_h(kd[5], A1, i ? B[2].z : B[2].x, i ? B[2].w : B[2].y);
                }
            }
            __syncwarp();
        };
        if (w >= 4 && KLAG) spin(t0 + KLAG);
        gen(0x1044);
        if (LATE) asm volatile("setmaxnreg.inc.sync.aligned.u32 %0;" ::"n"(RM));
        bar_sync(w < 7 ? 9 + w : 6, 64);
#pragma unroll 1
        for (uint32_t sel = 0x3244; sel < 0x8000; sel += 0x2200) {
            mul();
            gen(sel);
        }
        mul();
        TS(w == 0 ? 59 : w == 4 ? 60 : 63); T2S(1);
        {
#pragma unroll
            for (int nt = 0; nt < 3; nt++) stsm4(kt + nt * 512, kd[nt][0], kd[nt][1], kd[nt + 3][0], kd[nt + 3][1]);
            __syncwarp();
            uint4 R0 = lds128(st), R1 = lds128(st + 512), R2 = lds128(st + 1024);
            R0.x = hscl(R0.x); R0.y = hscl(R0.y); R0.z = hscl(R0.z); R0.w = hscl(R0.w);
            R1.x = hscl(R1.x); R1.y = hscl(R1.y); R1.z = hscl(R1.z); R1.w = hscl(R1.w);
            R2.x = hscl(R2.x); R2.y = hscl(R2.y); R2.z = hadd(hscl(R2.z), pk_h(bf_lo(Dsk) * __uint_as_float((370 - ex) << 23), 0.f));
            const bool l31 = lane == 31, l2 = lane < 2;
            uint32_t nx = __shfl_down_sync(~0u, R0.x, 1);
            if (l31) nx = R0.w >> 16;
            const uint32_t pr = __shfl_sync(~0u, l31 ? R0.w : R1.y, lane - 1);
            const uint32_t sA = __shfl_sync(~0u, R1.z, lane - 2), sB = __shfl_sync(~0u, R1.w, lane - 2);
            const uint32_t s0 = __shfl_sync(~0u, R2.x, lane - 2), s1 = __shfl_sync(~0u, R2.y, lane - 2);
            sts128(st + P_TAB + 32, __byte_perm(R0.y, R0.x, 0x5410), __byte_perm(R0.z, R0.y, 0x5410), __byte_perm(R0.w, R0.z, 0x5410), __byte_perm(R0.x, R0.w, 0x5432));
            sts128(st + P_TAB + PB + 32, __byte_perm(R0.y, R0.x, 0x7632), __byte_perm(R0.z, R0.y, 0x7632), __byte_perm(R0.w, R0.z, 0x7632), __byte_perm(R0.w, nx, 0x3254));
            const uint32_t d1 = __byte_perm(R1.y, 0, 0x1010), d3 = __byte_perm(R1.y, 0, 0x3232);
            sts128(st + P_TAB + 544, __byte_perm(pr, R1.x, 0x3254), __byte_perm(R1.y, R1.x, 0x5410), d1, d1);
            sts128(st + P_TAB + PB + 544, __byte_perm(R1.x, R1.y, 0x5432), __byte_perm(R1.y, R1.x, 0x7632), d3, d3);
            uint32_t a = w2;
            const uint32_t pA = l2 ? 0 : sA, pB = l2 ? sA : sB, pT = l2 ? sB : 0;
            sts64(a, __byte_perm(R1.z, pA, 0x5410), __byte_perm(R1.z, pA, 0x7632));
            sts64(a + 128, __byte_perm(R1.w, pB, 0x5410), __byte_perm(R1.w, pB, 0x7632));
            if (lane < 16) sts64(a + 256, pT << 16, pT & 0xffff0000u);
            a = w3;
            const uint32_t p0 = __byte_perm(0, s0, l2 ? 0x5432 : 0x7654), p1 = __byte_perm(s0, s1, l2 ? 0x5432 : 0x7654);
            sts32(a, __byte_perm(R2.x, p0, 0x5410)); sts32(a + 128, __byte_perm(R2.x, p0, 0x7632));
            sts32(a + 256, __byte_perm(R2.y, p1, 0x5410)); sts32(a + 384, __byte_perm(R2.y, p1, 0x7632));
            if (lane == 0) sts64(st + P_TAB + PB + 24, R2.z & 0xffffu, __byte_perm(R0.x, R2.z, 0x5410));
            if (l31) {
                sts64(st + P_TAB + 35 * 16, d3, d3 << 16);
                sts128(st + P_TAB + 39 * 16, 0, R1.w >> 16, __byte_perm(R1.w, 0, 0x3232), R1.w & 0xffff0000u);
            }
        }
        __syncwarp();
        TS(1); T2S(9);
        h4 acc[16] = {};
        const uint32_t t3 = t2 + T3 - T2, fo = st + 16, sc = (ex - 115) * 0x800080;
        auto put_tiles = [&](int i0, int i1, int bar) {
#pragma unroll
            for (int i = i0; i < i1; i++) {
                float d[4], e[4];
                mma_cvt(d, acc[2 * i], Id);
                mma_cvt(e, acc[2 * i + 1], Id);
                stsm4t(aB + (2 * i - 1) * TS8, bmul(pk_bf(d[0], d[1]), sc), bmul(pk_bf(d[2], d[3]), sc), bmul(pk_bf(e[0], e[1]), sc), bmul(pk_bf(e[2], e[3]), sc));
            }
            __syncwarp();
            mbar_arrive_e(sb + B_Y + bar * 8);
        };
        auto filter = [&](int p) {
            const uint32_t ac = ac0 + p * 4 * TS8;
            const uint4 q2 = lds128(ac), q3 = lds128(ac + 16);
            const uint32_t cy = p ? lds32(cyP + 512) : 0;
            const uint2 q0 = lds64(ac - BS + 8);
            const uint4 q1 = lds128(ac - BS + 16);
            __syncwarp();
            if (!ORD || p == 2) put_tiles(2 * p, 2 * p + 2, p);
            sts32(cyP, cy);
            const uint32_t U[13] = {q0.x, q0.y, q1.x, q1.y, q1.z, q1.w, q2.x, q2.y, q2.z, q2.w, q3.x, q3.y, q3.z};
            uint32_t Q[13], Pp[12], P4[12], C3[12], C5[10];
#pragma unroll
            for (int k = 1; k < 13; k++) Q[k] = __byte_perm(U[k - 1], U[k], 0x5432);
#pragma unroll
            for (int k = 1; k < 12; k++) Pp[k] = hadd(U[k], Q[k]);
#pragma unroll
            for (int k = 2; k < 12; k++) P4[k] = hadd(Pp[k], Pp[k - 1]);
#pragma unroll
            for (int k = 3; k < 12; k++) C3[k] = hadd(Pp[k], Q[k + 1]);
#pragma unroll
            for (int k = 1; k < 10; k++) C5[k] = hadd(P4[k + 1], U[k - 1]);
            if (p < 2)
#pragma unroll
                for (int h = 0; h < 2; h++) {
                    const int k = 2 + 4 * h;
                    sts128(fo + (4 + h) * 528, hadd(P4[k], C3[k + 1]), hadd(P4[k + 1], C3[k + 2]), hadd(P4[k + 2], C3[k + 3]), hadd(P4[k + 3], C3[k + 4]));
                    sts128(fo + (6 + h) * 528, hadd(P4[k + 2], C5[k - 1]), hadd(P4[k + 3], C5[k]), hadd(P4[k + 4], C5[k + 1]), hadd(P4[k + 5], C5[k + 2]));
                }
            sts128(fo, C3[4], C3[5], C3[6], C3[7]); sts128(fo + 528, C3[8], C3[9], C3[10], C3[11]);
            sts128(fo + 2 * 528, C5[2], C5[3], C5[4], C5[5]); sts128(fo + 3 * 528, C5[6], C5[7], C5[8], C5[9]);
            __syncwarp();
        };
        uint2 T[5], U2[5], V[8];
        auto coarse = [&](int p, bool load) {
            if (load)
#pragma unroll
                for (int D = 0; D < 5; D++) if (p < 2 || D < 4) T[D] = lds64(t2 + D * 64);
#pragma unroll
            for (int gl = 0; gl < 4; gl++) {
                const uint4 A = ldsm4t(fa + gl * 128);
#pragma unroll
                for (int D = 0; D < 5; D++) if (4 * p + gl + D + 4 < 16) mma_h(acc[4 * p + gl + D + 4], A, T[D].x, T[D].y);
            }
            if (load) {
#pragma unroll
                for (int D = 0; D < 5; D++) if (p < 2 || D < 4) U2[D] = lds64(t2 + 320 + D * 64);
#pragma unroll
                for (int D = 0; D < 8 - 4 * p; D++) V[D] = lds64(t3 + D * 64);
            }
#pragma unroll
            for (int gl = 0; gl < 4; gl++) {
                const uint4 A = ldsm4t(fb + gl * 128);
#pragma unroll
                for (int D = 0; D < 5; D++) if (4 * p + gl + D + 4 < 16) mma_h(acc[4 * p + gl + D + 4], A, U2[D].x, U2[D].y);
                if (p < 2) {
                    const uint4 A3 = ldsm4t(fc + gl * 128);
#pragma unroll
                    for (int D = 7; D >= 0; D--) if (4 * p + gl + D + 8 < 16) mma_h(acc[4 * p + gl + D + 8], A3, V[D].x, V[D].y);
                }
            }
        };
        T2S(10);
        if (!ORD) conv_half<true>(acc, a1, aB, ac0 - BS + 16, sb + B_RAW, Zr);
        else mbar_wait(sb + B_RAW);
        T2S(11);
        filter(0);
        coarse(0, true);
        filter(1);
        coarse(1, false);
        T2S(12);
        if (ORD) {
            conv_half<true>(acc, a1, aB, ac0 - BS + 16, sb + B_RAW, Zr);
            __syncwarp();
            put_tiles(0, 2, 0);
            put_tiles(2, 4, 1);
        }
        T2S(22);
        conv_half<false>(acc, a1, aB + 8 * TS8, ac0 - BS + 16 + 8 * TS8, sb + B_RAW + 8, Zr);
        T2S(23);
        filter(2);
        coarse(2, !TKEEP);
        put_tiles(6, 7, 3);
        put_tiles(7, 8, 4);
        T2S(24);
        TS(3);
        TDUMP;
    } else if (w < 16) {
        LANES;
        const int hw = w - 8;
        if (RH < 96) asm volatile("setmaxnreg.dec.sync.aligned.u32 %0;" ::"n"(RH));
        if (RH > 96) asm volatile("setmaxnreg.inc.sync.aligned.u32 %0;" ::"n"(RH));
        uint32_t tag;
        asm volatile("ld.relaxed.gpu.global.u32 %0,[%1];" : "=r"(tag) : "l"(prm.S->epoch + b) : "memory");
        tag = ~tag << 31;
        {
            uint32_t W[16];
#pragma unroll
            for (int k = 0; k < 4; k++) {
                const uint4 v = ldg128(prm.wr + hw * 16 + (k ^ (g & 1)) * 4 + c);
                W[4 * k] = v.x; W[4 * k + 1] = v.y; W[4 * k + 2] = v.z; W[4 * k + 3] = v.w;
            }
#pragma unroll
            for (int k = 0; k < 16; k++) if (g & 2) W[k] = 0x3f803f80u;
            const bool dg = mi == c, od = g & 1;
            uint32_t ra = sb + O_ROWS + g * 2048 + hw * 256 + od * 64 + c * 16;
            uint32_t pa = sb + O_PST + ((dg ? 0 : 8 + 4 * (g & 2)) + 2 * c + od) * 48 + hw * 4;
            TS(hw == 4 ? 22 : 63);
            bar_sync(3, 288);
#pragma unroll 1
            for (int hf = 0; hf < 2; hf++) {
                float d[4] = {}, e[4] = {};
                mbar_wait(sb + B_ROW + hf * 8);
                TS(hw == 4 ? (hf ? 23 : 58) : 63);
#pragma unroll
                for (int k = 0; k < 4; k++) {
                    const uint4 x = lds128((ra ^ ((k & 1) << 6)) + (k >> 1) * 128);
                    mma_bf(d, x.x ^ Z, W[4 * k], x.y ^ Z, W[4 * k + 1], x.x, x.y);
                    mma_bf(e, x.z ^ Z, W[4 * k + 2], x.w ^ Z, W[4 * k + 3], x.z, x.w);
                }
#define PICK2(e) (dg ? (od ? e[1] : e[0]) : (od ? e[3] : e[2]))
                sts32(pa, __float_as_uint(PICK2(d) + PICK2(e)));
                TS(hf ? 63 : 8 + hw);
                bar_arrive(1 + 3 * hf, 288);
                ra += 16384; pa += 1152;
            }
        }
        const int n0 = hw + (hw & 4);
        const uint32_t tok = n0 * 16 + (lane & 2) * 32 + (lane & 1) * 8 + g, xo = O_XT + lane * 32 + ((rk ^ g) & 1) * 16;
        const uint32_t ta = sb + O_RAW + (n0 + (r8 & 4)) * BS + (mi ^ 1) * 64 + (r8 & 1) * 32 + (r8 & 2) * 8;
        const uint2* sp = prm.S->stats + (b & 3) * 2048 + tok;
        uint4 x[8];
        uint2 u[8];
        uint32_t G[32];
        float h[32];
        auto load = [&](int hf) {
            mbar_wait(sb + B_X + hf * 8);
#pragma unroll
            for (int i = 4 * hf; i < 4 * hf + 4; i++) x[i] = lds128(sb + xo + hw * 1024 + (i & 3) * 8192 + hf * (O_XB - O_XT));
        };
        auto poll = [&](int hf) {
            mbar_wait(sb + B_GO + hf * 8);
            TS(hw == 3 ? 16 + hf : 63);
            const uint2* v = u + 4 * hf;
            int it = 0;
#pragma unroll 1
            do {
#pragma unroll
                for (int i = 4 * hf; i < 4 * hf + 4; i++) u[i] = ldr64(sp + i * 256);
            } while (__any_sync(~0u, (int)(((v[0].x ^ tag) | (v[1].x ^ tag)) | ((v[2].x ^ tag) | (v[3].x ^ tag))) < 0) && ++it < 100000);
            TV(hw == 7 ? 61 + hf : 63, it);
            TS(hw == 3 ? (hf ? 25 : 18) : 63);
        };
        auto norm = [&](int i0) {
#pragma unroll
            for (int i = i0; i < i0 + 2; i++) {
                const float r = fabsf(__uint_as_float(u[i].x));
                float* v = h + 8 * (i & 3);
#pragma unroll
                for (int k = 0; k < 4; k++) {
                    const uint32_t e = bsub_lo(comp(x[i], k), u[i].y);
                    v[2 * k] = bf_lo(e) * r; v[2 * k + 1] = bf_hi(e) * r;
                }
                stsm4t(ta + i * 2 * TS8, pk_h(v[2], v[3]), pk_h(v[0], v[1]), pk_h(v[6], v[7]), pk_h(v[4], v[5]));
            }
            if (i0 & 2) { __syncwarp(); mbar_arrive_e(sb + B_RAW + (i0 & 4) * 2); }
        };
        auto gate = [&](int i0) {
            uint32_t* v = G + 4 * i0;
            const float* e = h + 8 * (i0 & 3);
#pragma unroll
            for (int k = 0; k < 8; k++) v[k] = pk_bf(fmaf(e[2 * k], ftanh(e[2 * k]), e[2 * k]), fmaf(e[2 * k + 1], ftanh(e[2 * k + 1]), e[2 * k + 1]));
            pin4(v[0], v[1], v[2], v[3], Z); pin4(v[4], v[5], v[6], v[7], Z);
        };
        load(0); poll(0); norm(0); norm(2);
        TS(32 + hw);
        sched_fence(Z);
        gate(0); gate(2);
        TS(hw == 0 ? 20 : 63);
        load(1);
        pin4(x[7].x, x[7].y, x[7].z, x[7].w, Z);
        mbar_arrive_e(sb + B_XR);
        poll(1);
        mbar_wait(sb + B_XR);
        norm(4); gate(4);
        sched_fence(Z);
        norm(6);
        TS(hw == 3 ? 19 : 63);
        gate(6);
        TS(hw == 0 ? 21 : 63);
        if (RH2 < RH) asm volatile("setmaxnreg.dec.sync.aligned.u32 %0;" ::"n"(RH2));
        mbar_wait(sb + B_SEL);
        mbar_wait(sb + B_SEL + 8);
        if (hw == 0) {
            mbar_arrive_peer_e(pb + B_XF);
            if (lane == 0) prm.S->epoch[b] = lds32(sb + O_SEL + 32);
        }
        const uint32_t r0 = lds32(sb + O_SEL) - tok, r1 = lds32(sb + O_SEL + 16) - tok;
        const uint32_t mine = ((r0 & 255) ? 0 : 128 << (r0 >> 8)) | ((r1 & 255) ? 0 : 128 << (r1 >> 8));
        const uint32_t skip = __reduce_or_sync(~0u, mine);
        const bool loc = (hw >> 2) == rk;
        const uint32_t oa = (loc ? sb : pb) + xo + (hw & 3) * 1024, ob = B_O + (hw & 3) * 40;
        if (!loc) mbar_wait(sb + B_XF);
#pragma unroll
        for (int p = 0; p < 5; p++) {
            const int i0 = p < 4 ? 2 * p : 7, i1 = p < 3 ? 2 * p + 2 : p + 4;
            if (loc) mbar_expect_e(sb + ob + p * 8, (i1 - i0) * 512);
            if (p == 3 && b < NFFN) mbar_wait(sb + B_HR);
            mbar_wait(sb + B_Y + p * 8);
            TS(hw == 1 ? 26 + p : 63);
#pragma unroll
            for (int i = i0; i < i1; i++) {
                const uint4 s = ldsm4t(ta + (2 * i - 1) * TS8);
                x[i] = make_uint4(bfma(s.y, G[4 * i], x[i].x), bfma(s.x, G[4 * i + 1], x[i].y), bfma(s.w, G[4 * i + 2], x[i].z), bfma(s.z, G[4 * i + 3], x[i].w));
            }
            if (loc) {
#pragma unroll
                for (int i = i0; i < i1; i++) sts128(oa + i * 4096, x[i].x, x[i].y, x[i].z, x[i].w);
                mbar_wait(sb + ob + p * 8);
                TS(p == 4 ? 120 + hw : 63);
                fence_async();
                __syncwarp();
#pragma unroll
                for (int i = i0; i < i1; i++) {
                    tma5d_st_e(sb + O_XT + (hw & 3) * 1024 + i * 4096, &mo, q * 16, 4 * i + 2 * rk + ((skip >> i) & 128), hw & 3);
                }
            } else {
#pragma unroll
                for (int i = i0; i < i1; i++) st_async(oa + i * 4096, x[i], pb + ob + p * 8);
            }
        }
        if (skip) {
#pragma unroll
            for (int i = 0; i < 8; i++)
                if ((skip & ~mine) >> (7 + i) & 1) prm.out[(tok + i * 256) * 128 + b] = x[i];
        }
        asm volatile("cp.async.bulk.commit_group; cp.async.bulk.wait_group.read 0;" ::: "memory");
        TS(40 + hw);
        TDUMP;
    } else {
        asm volatile("setmaxnreg.dec.sync.aligned.u32 %0;" ::"n"(480 - 2 * RM - 2 * RH));
        LANES;
        const int fw = w - 16;
        const CUtensorMap* m1 = &mg + rk;
        if (fw == 0) {
            asm volatile("{.reg .pred p; elect.sync _|p,0xffffffff; @p mbarrier.init.shared.b64 [%0],1; @p mbarrier.init.shared.b64 [%0+8],1; fence.mbarrier_init.release.cluster;\n"
                         "@p mbarrier.arrive.expect_tx.shared.b64 _,[%0],16384; @p mbarrier.arrive.expect_tx.shared.b64 _,[%0+8],16384;}" ::"r"(sb + B_ROW) : "memory");
            bar_arrive(5, 128);
            spin(t0 + ROW0);
            bulk_e(sb + O_ROWS, prm.u + b * 1024, sb + B_ROW, 16384);
            TS(6); TV(0, t0 & 0xfffff);
            spin(t0 + ROW1);
            bulk_e(sb + O_ROWS + 16384, prm.u + (128 + b) * 1024, sb + B_ROW + 8, 16384);
            bar_sync(7, 64);
            if (b < NFFN) {
#pragma unroll 1
                for (int i = 0; i < 12; i++) {
                    spin(t0 + W0 + ((b * WD) >> 7) + min(i, NPE) * WD);
                    if (i == 4) mbar_wait(sb + B_P1);
                    if (i == 10) mbar_wait(sb + B_XR);
                    tma3d_e(sb + (i < 8 ? O_RING + i * 8192 : O_RNG3 + ((i + 2) & 3) * 8192), m1, i * 64, q, sb + B_FULL + i * 8);
                }
            }
        } else {
            if (lane == 0) {
#pragma unroll
                for (int i = 0; i < 21; i++)
                    asm volatile("mbarrier.init.shared.b64 [%0],%1;" ::"r"(sb + B_FULL - 8 + 8 * fw + i * 24), "r"(i < 18 ? 1 : 8) : "memory");
            }
            __syncwarp();
            asm volatile("fence.mbarrier_init.release.cluster; barrier.cluster.arrive.relaxed.aligned;" ::: "memory");
            asm volatile("prefetch.tensormap [%0];" ::"l"(&md - 1 + fw));
            asm volatile("prefetch.tensormap [%0];" ::"l"(m1));
            bar_sync(5, 128);
            if (fw == 2)
#pragma unroll
                for (int i = 0; i < 8; i++) bar_arrive(i < 7 ? 9 + i : 6, 64);
            if (fw == 1) {
                bar_arrive(3, 288);
                bar_arrive(7, 64);
                mbar_expect_e(sb + B_H, 256);
                mbar_expect_e(sb + B_X, 32768);
                mbar_expect_e(sb + B_X + 8, 32768);
                asm volatile("barrier.cluster.wait.aligned;" ::: "memory");
#pragma unroll 1
                for (int i = 0; i < 8; i++) {
                    spin(t0 + (i < 4 ? GAT0 + i * GATD : GAT1 + (i & 3) * GATE));
                    tma5d_mc_e(sb + (i < 4 ? O_XT : O_XB) + (i & 3) * 8192 + rk * 4096, &mx, q * 16, i * 4 + rk * 2, sb + B_X + (i & 4) * 2);
                }
            }
        }
        if (fw == 2) {
            sts32(sb + O_ONE + lane * 4, 0x3f803f80u);
            __syncwarp();
            mbar_expect_e(sb + B_XS, 4096);
            spin(t0 + TGO0);
            mbar_arrive_e(sb + B_GO);
        }
        if (fw == 3) {
            uint32_t ep;
            asm volatile("ld.relaxed.gpu.global.u32 %0,[%1];" : "=r"(ep) : "l"(prm.S->epoch + b) : "memory");
            ep += 1;
            sts32(sb + O_SEL + 32, ep);
            float sw[4] = {0.f, 0.f, 0.f, 0.f};
#pragma unroll
            for (int k = 0; k < 4; k++) mma_bf(sw, ldg128(prm.wr + k * 32 + lane), 0x3f803f80u, 0x3f803f80u);
            float wsum = sw[0] + sw[2];
#pragma unroll
            for (int o = 4; o < 32; o <<= 1) wsum += __shfl_xor_sync(~0u, wsum, o);
            uint2* dst = prm.S->stats + c * 2048 + b * 8 + g;
            uint32_t pa = sb + O_PST + g * 48 + (lane & 1) * 16, ky = 0;
            const uint32_t id = (ep & 1) * 0x8000 + 2047 - (lane & 1) * 1024 - b * 8 - g;
#pragma unroll 1
            for (int hf = 0; hf < 2; hf++) {
                bar_sync(1 + 3 * hf, 288);
                float v[3];
#pragma unroll
                for (int k = 0; k < 3; k++) {
                    const uint4 t = lds128(pa + k * 384);
                    v[k] = (__uint_as_float(t.x) + __uint_as_float(t.y)) + (__uint_as_float(t.z) + __uint_as_float(t.w));
                    v[k] += __shfl_xor_sync(~0u, v[k], 1);
                }
                const float mean = v[2] * (1.f / 1024.f);
                const float var = fmaxf(fmaf(-mean, mean, v[0] * (1.f / 1024.f)), 0.f);
                const float rs = rcp(bfr(fsqrt(bfr(bfr(var) + 1e-5f))));
                const uint32_t mk = pk_bf(mean, fmaf(-bfr(mean), wsum, v[1]) * rs);
                str64(dst, __float_as_uint(0.5f * rs) | ep << 31, mk);
                if ((lane & 1) == hf) ky = ((mk ^ (((int)mk >> 31) | 0x80000000u)) & 0xffff0000u) | id;
                TS(hf ? 63 : 5);
                dst += 1024; pa += 1152;
            }
            const uint32_t k1 = __reduce_max_sync(~0u, ky), k2 = __reduce_max_sync(~0u, ky == k1 ? 0u : ky);
            str64(prm.S->keys + g * 128 + b, k1, k2);
            TS(48);
            mbar_arrive_e(sb + B_P1);
        }
        uint32_t wa[4];
#pragma unroll
        for (int i = 0; i < 4; i++) wa[i] = sb + O_RING + fw * 8192 + ((mi >> 1) * 8 + r8) * 128 + (((2 * i + (mi & 1)) ^ r8) << 4);
        uint32_t xs = sb + mi * 16 + ((r8 & 2) ? O_ONE : O_XSEL + fw * 128 + (r8 & 1) * 2064), xd = (r8 & 2) ? 0 : 512;
        uint32_t dst = ((rk * 32 + fw * 4 + c) * 112 + q) * 8 + g, hs = sb + O_HT + (r8 & 1) * 144 + mi * 16;
        pin4(wa[0], wa[1], wa[2], wa[3], Z); pin4(xs, xd, dst, hs, Z);
        mbar_wait(sb + B_P1);
        const uint32_t ep = lds32(sb + O_SEL + 32);
        if (fw >= 2) {
            const uint2* kp = prm.S->keys + ((b & 3) * 2 + (fw & 1)) * 128 + lane * 2;
            const uint32_t tag = ep << 15;
            mbar_wait(sb + B_RAW);
            spin(t0 + TTOP);
            uint4 k, l;
            int it = 0;
#pragma unroll 1
            do { k = ldr128(kp); l = ldr128(kp + 64); } while (__any_sync(~0u, (((k.x ^ tag) | (k.z ^ tag)) | ((l.x ^ tag) | (l.z ^ tag))) & 0x8000) && ++it < 100000);
            TV(fw == 2 ? 24 : 63, it);
            TS(fw == 2 ? 49 : 63);
            uint32_t ky = __reduce_max_sync(~0u, max(max(k.x, k.z), max(l.x, l.z)));
            if (fw & 1) ky = __reduce_max_sync(~0u, max(max(k.x == ky ? k.y : k.x, k.z == ky ? k.w : k.z), max(l.x == ky ? l.y : l.x, l.z == ky ? l.w : l.z)));
            const uint32_t tok = ~ky & 2047;
            if (b < NFFN) bulk_e(sb + O_XSEL + (fw & 1) * 2064, prm.u + tok * 128, sb + B_XS, 2048);
            sched_fence(Z);
            if (fw == 3) mbar_arrive_e(sb + B_GO + 8);
            uint2 rc;
#pragma unroll 1
            do rc = ldr64(prm.S->stats + (b & 3) * 2048 + tok); while (__any_sync(~0u, (int)(rc.x ^ tag << 16) < 0) && ++it < 100000);
            sts128(sb + O_SEL + (fw & 1) * 16, tok, pk_bf(0.f, sigm(bf_hi(ky ^ (~((int)ky >> 31) | 0x80000000u)))), rc.y << 16, __float_as_uint(2.f * fabsf(__uint_as_float(rc.x))));
            __syncwarp();
            mbar_arrive_e(sb + B_SEL + (fw & 1) * 8);
        }
        if (b < NFFN) {
            float h[4][4] = {};
            uint4 A[8], B[2];
            const bool c1 = c & 1, c2 = c & 2;
            const uint32_t s2 = O_RNG3 + ((fw ^ 2) - fw) * 8192, bf = sb + B_FULL + fw * 8;
#define SLOT(n) ((n) % 3 == 2 ? s2 : (n) % 3 * 32768)
            auto ldA = [&](int k, int n, int hf) { A[k] = ldsm4t(wa[k & 3] + SLOT(n) + hf * 4096 + (k >> 2) * 2048); };
            auto half = [&](const uint4& x, int n, int hf) {
                sched_fence(Z);
#pragma unroll
                for (int k = 0; k < 8; k++) {
                    mma_bf(h[k & 3], A[k], k < 4 ? x.x : x.z, k < 4 ? x.y : x.w);
                    if (n >= 0) ldA(k, n, hf);
                }
            };
            mbar_wait(bf);
#pragma unroll
            for (int k = 0; k < 8; k++) ldA(k, 0, 0);
            mbar_wait(sb + B_XS);
            TS(fw == 1 ? 50 : 63);
            B[0] = ldsm4(xs);
#pragma unroll
            for (int n = 0; n < 4; n++) {
                TS(64 + fw + 4 * n);
                B[1] = ldsm4(xs + 64);
                half(B[0], n, 1);
                xs += xd;
                if (n < 3) { mbar_wait(bf + 32 * n + 32); B[0] = ldsm4(xs); }
                half(B[1], n < 3 ? n + 1 : -1, 0);
                TS(96 + fw + 4 * n);
                if (n < 3) {
                    sched_fence(Z);
                    if (n >= PACE) spin(t0 + W0 + ((b * WD) >> 7) + (fw + 4 * n + 12 - LEAD) * WD);
                    tma3d_e(sb + O_RING + fw * 8192 + SLOT(n), n ? &md : m1, (n ? q : fw + 12) * 64, n ? rk * 8 + fw + 4 * n - 4 : q, bf + 32 * n + 96);
                }
            }
#pragma unroll
            for (int j = 0; j < 4; j += 2)
                sts128(sb + O_RING + fw * 8192 + j * 256 + lane * 16, __float_as_uint(c2 ? h[j + 1][0] : h[j][0]), __float_as_uint(c2 ? h[j + 1][1] : h[j][1]),
                       __float_as_uint(c2 ? h[j + 1][2] : h[j][2]), __float_as_uint(c2 ? h[j + 1][3] : h[j][3]));
            if (fw >= 2) {
                bar_arrive(2, 128);
            } else {
                const uint32_t pa = sb + O_RING + fw * 512 + (lane >> 1) * 32 + (lane & 1) * 8, ha = sb + O_HT + fw * 64 + c * 16 + g * 2;
                mbar_wait(sb + B_SEL);
                mbar_wait(sb + B_SEL + 8);
                mbar_wait(sb + B_XF);
                const uint2 n0 = lds64(sb + O_SEL + 8), n1 = lds64(sb + O_SEL + 24);
                bar_sync(2, 128);
                TS(fw == 0 ? 51 : 63);
                float t[3][4];
#pragma unroll
                for (int j = 0; j < 4; j++) {
                    const uint2 p = lds64(pa + j * 8192);
                    t[0][j] = __uint_as_float(p.x); t[1][j] = __uint_as_float(p.y); t[2][j] = __uint_as_float(lds32(pa + j * 8192 + 16));
                }
                const float cs = (t[2][0] + t[2][1]) + (t[2][2] + t[2][3]);
                uint32_t v = pk_bf(fmaf(-__uint_as_float(n0.x), cs, (t[0][0] + t[0][1]) + (t[0][2] + t[0][3])) * __uint_as_float(n0.y),
                                   fmaf(-__uint_as_float(n1.x), cs, (t[1][0] + t[1][1]) + (t[1][2] + t[1][3])) * __uint_as_float(n1.y));
                if (rk == 0) v = pk_bf(silu(bf_lo(v)), silu(bf_hi(v)));
                asm volatile("st.async.shared::cluster.mbarrier::complete_tx::bytes.b32 [%0],%1,[%2];" ::"r"(pb + O_HX + fw * 128 + lane * 4), "r"(v), "r"(pb + B_H) : "memory");
                mbar_wait(sb + B_H);
                v = bmul(v, lds32(sb + O_HX + fw * 128 + lane * 4));
                sts16(ha, v); sts16(ha + 144, v >> 16);
                __syncwarp();
                asm volatile("{.reg .pred p; elect.sync _|p,0xffffffff; @p mbarrier.arrive.shared.b64 _,[%0],4;}" ::"r"(sb + B_HR) : "memory");
            }
#pragma unroll
            for (int n = 4; n < 6; n++) {
                mbar_wait(bf + 32 * n);
                TS(64 + fw + 4 * n);
#pragma unroll
                for (int k = 0; k < 8; k++) ldA(k, n, 0);
                if (n == 4) {
                    mbar_wait(sb + B_HR);
                    TS(fw == 0 ? 52 : 63);
                    B[0] = ldsm4(hs); B[1] = ldsm4(hs + 64);
                }
#pragma unroll
                for (int k = 0; k < 16; k++) h[k >> 2][k & 3] = 0.f;
                half(B[0], n, 1);
                half(B[1], -1, 0);
#define PICK(k) __float_as_uint(c2 ? (c1 ? h[3][k] : h[2][k]) : (c1 ? h[1][k] : h[0][k]))
                uint2* yo = prm.S->yp + dst + (n - 4) * 16 * 112 * 8;
                str64(yo, (PICK(0) & ~1u) | (ep & 1), PICK(1)); str64(yo + 448, (PICK(2) & ~1u) | (ep & 1), PICK(3));
                TS(96 + fw + 4 * n);
            }
            TS(fw == 0 ? 63 : 52 + fw);
        }
        if (!NOFIX && fw == 0) {
            mbar_wait(sb + B_SEL);
            mbar_wait(sb + B_SEL + 8);
            const uint4 sel = lds128(sb + O_SEL + (lane & 8) * 2);
            const uint32_t ch = 2 * c + (g & 1), go = sel.x * 1024 + b * 8 + ch;
            uint32_t xv;
            uint32_t sa = sb + O_RAW - TS8 + (sel.x >> 4) * BS + ch * 32 + (sel.x & 15) * 2;
            uint32_t ba = __reduce_max_sync(~0u, sel.x >> 8);
            ba = sb + B_Y + (ba == 7 ? 4 : ba >> 1) * 8;
            asm volatile("ld.global.nc.u16 %0,[%1];" : "=r"(xv) : "l"((const uint16_t*)prm.u + go) : "memory");
            xv <<= 16;
            uint32_t j0 = 0, xn = __float_as_uint(bfr(bfr(__uint_as_float(xv) - __uint_as_float(sel.z)) * __uint_as_float(sel.w)));
            pin4(xv, xn, sa, j0, Z);
            const uint4* yp = (const uint4*)prm.S->yp + b * 224 + lane;
            spin(t0 + TFIX);
            uint4 v[7];
            int it = 0;
            uint32_t bad, sv;
#pragma unroll 1
            do {
#pragma unroll
                for (int j = 0; j < 7; j++) v[j] = ldr128(yp + j * 32);
                mbar_wait(ba);
                sv = lds16(sa);
                bad = 0;
#pragma unroll
                for (int j = 0; j < 7; j++) asm volatile("{.reg .b32 t; lop3.b32 t,%1,%2,%3,0x7e; or.b32 %0,%0,t;}" : "+r"(bad) : "r"(v[j].x), "r"(ep), "r"(v[j].z));
            } while (__any_sync(~0u, bad & 1) && ++it < 100000);
            TV(57, it);
            float y[4];
#pragma unroll
            for (int k = 0; k < 4; k++)
                y[k] = ((__uint_as_float(comp(v[0], k)) + __uint_as_float(comp(v[1], k))) + (__uint_as_float(comp(v[2], k)) + __uint_as_float(comp(v[3], k)))) +
                       ((__uint_as_float(comp(v[4], k)) + __uint_as_float(comp(v[5], k))) + __uint_as_float(comp(v[6], k)));
            const bool b2 = lane & 4, b3 = lane & 8;
            const float y0 = (b2 ? y[2] : y[0]) + __shfl_xor_sync(~0u, b2 ? y[0] : y[2], 4), y1 = (b2 ? y[3] : y[1]) + __shfl_xor_sync(~0u, b2 ? y[1] : y[3], 4);
            float t = (b3 ? y1 : y0) + __shfl_xor_sync(~0u, b3 ? y0 : y1, 8);
            t += __shfl_xor_sync(~0u, t, 16);
            const float gt = bfr(silu(bfr(__uint_as_float(xn) + bfr(bfr(t) * __uint_as_float(sel.y)))));
            TS(56);
            ((uint16_t*)prm.out)[go] = pk_bf(fmaf(bf_lo(sv), gt, __uint_as_float(xv)), 0.f);
            TS(7);
        }
        TDUMP;
    }
}

typedef CUresult (*EncFn)(CUtensorMap*, CUtensorMapDataType, cuuint32_t, void*, const cuuint64_t*, const cuuint64_t*,
                          const cuuint32_t*, const cuuint32_t*, CUtensorMapInterleave, CUtensorMapSwizzle,
                          CUtensorMapL2promotion, CUtensorMapFloatOOBfill);

void make_map(EncFn f, CUtensorMap* m, const void* p, int rank, const cuuint64_t* gd, const cuuint64_t* gs,
              const cuuint32_t* bd, CUtensorMapSwizzle sw) {
    const cuuint32_t es[5] = {1, 1, 1, 1, 1};
    f(m, CU_TENSOR_MAP_DATA_TYPE_BFLOAT16, rank, const_cast<void*>(p), gd, gs, bd, es, CU_TENSOR_MAP_INTERLEAVE_NONE, sw,
      CU_TENSOR_MAP_L2_PROMOTION_NONE, CU_TENSOR_MAP_FLOAT_OOB_FILL_NONE);
}

}

extern "C" void kernel_launch(void* const* d_in, const int* in_sizes, int n_in, void* d_out, int out_size) {
    (void)in_sizes; (void)n_in; (void)out_size;
    void* fp = nullptr;
    cudaDriverEntryPointQueryResult qr;
    cudaGetDriverEntryPoint("cuTensorMapEncodeTiled", &fp, cudaEnableDefault, &qr);
    EncFn enc = (EncFn)fp;
    Maps maps;
    CUtensorMap &mg = maps.m[0], &mu = maps.m[1], &md = maps.m[2], &mx = maps.m[3], &mo = maps.m[4];
    {
        const cuuint64_t gd[3] = {64, 1024, 56}, gs[2] = {7168, 128};
        const cuuint32_t bd[3] = {64, 64, 1};
        make_map(enc, &mg, d_in[9], 3, gd, gs, bd, CU_TENSOR_MAP_SWIZZLE_128B);
        make_map(enc, &mu, d_in[10], 3, gd, gs, bd, CU_TENSOR_MAP_SWIZZLE_128B);
    }
    {
        const cuuint64_t gd[3] = {64, 3584, 16}, gs[2] = {2048, 128};
        const cuuint32_t bd[3] = {64, 64, 1};
        make_map(enc, &md, d_in[11], 3, gd, gs, bd, CU_TENSOR_MAP_SWIZZLE_128B);
    }
    {
        const cuuint64_t gd[5] = {1024, 2, 32, 8, 4}, gs[4] = {16384, 131072, 2048, 32768};
        const cuuint32_t bd[5] = {16, 2, 2, 8, 4}, bo[5] = {16, 2, 2, 8, 1};
        make_map(enc, &mx, d_in[0], 5, gd, gs, bd, CU_TENSOR_MAP_SWIZZLE_32B);
        make_map(enc, &mo, d_out, 5, gd, gs, bo, CU_TENSOR_MAP_SWIZZLE_32B);
    }
    Params p;
    p.u = (const uint4*)d_in[0]; p.logA = (const uint2*)d_in[1]; p.Aim = (const uint2*)d_in[2];
    p.Cre = (const uint2*)d_in[3]; p.Cim = (const uint2*)d_in[4];
    p.logdt = (const uint16_t*)d_in[5]; p.Dsk = (const uint16_t*)d_in[6]; p.wr = (const uint4*)d_in[8];
    p.out = (uint4*)d_out;
    void* sp = nullptr;
    cudaGetSymbolAddress(&sp, g_scratch);
    p.S = (Scratch*)sp; p.zero = 0;
    cudaFuncSetAttribute(fused_kernel, cudaFuncAttributeMaxDynamicSharedMemorySize, SMEM_BYTES + 512);
    fused_kernel<<<128, 640, SMEM_BYTES + 512, cudaStreamPerThread>>>(p, maps);
}
```

```cpp
#include <cuda_runtime.h>
#include <cuda_bf16.h>
#include <cuda_fp16.h>
#include <cuda.h>
#include <stdint.h>

#define RM 120
#define RH 80
#define ORD 1
#define FSB 1
#define RH2 RH
#define RF2 (480 - 2 * RM - 2 * RH2)
#define KV 5
#define FM 1023
#define SBC 1
#define LATE 1
#define KLAGV 0
#define PSY 0
#define NOFIX 0
#define NFFN 112
namespace {

constexpr int RING = 8;
constexpr uint32_t BS = 272, TS8 = 8 * BS;
constexpr uint32_t O_RING = 0;
constexpr uint32_t O_XT   = RING * 8192;
constexpr uint32_t O_RAW  = O_XT + 32768 + TS8;
constexpr uint32_t O_XB   = O_RAW + 8 * TS8 + 128;
constexpr uint32_t O_HX   = O_RAW + 16 * TS8;
constexpr uint32_t O_HT   = O_HX + 256;
constexpr uint32_t O_RNG3 = 133 * 1024;
constexpr uint32_t O_PST  = O_RNG3 + 3 * 8192;
constexpr uint32_t O_PRIV = O_RNG3 + 32768;
constexpr uint32_t PRIV   = 7744;
constexpr uint32_t P_TAB  = 4224;
constexpr uint32_t O_XSEL = O_XT + 6 * 4096;
constexpr uint32_t O_ROWS = (RING - 4) * 8192;
constexpr uint32_t O_SEL  = O_PRIV + 8 * PRIV;
constexpr uint32_t O_ONE  = O_SEL + 64;
constexpr uint32_t O_BAR  = O_ONE + 128;
constexpr uint32_t B_ROW = O_BAR, B_FULL = B_ROW + 16, B_H = B_FULL + 8 * 24, B_SEL = B_H + 8, B_P1 = B_SEL + 16,
                   B_X = B_P1 + 8, B_GO = B_X + 16, B_XS = B_GO + 16, B_XF = B_XS + 8, B_O = B_XF + 8, B_Y = B_O + 160, B_RAW = B_Y + 40, B_HR = B_RAW + 16, B_XR = B_HR + 8;
constexpr uint32_t SMEM_BYTES = B_Y + 72;
static_assert(B_Y - B_FULL == 18 * 24 && O_XB % 256 == 0 && O_HT + 288 <= O_RNG3 && O_XB + 32768 <= O_RNG3 + 16384, "layout");
static_assert(SMEM_BYTES + 512 <= 232448, "smem");
constexpr int PB = 1216, T2 = 2368, T3 = T2 + 640;

#define SCHED(X) X(0, ROW0, 330) X(1, ROW1, 1020) X(2, NPE, 11) X(3, GAT0, 900) X(4, GAT1, 2200) X(5, GATD, 60) X(6, TGO0, 2850) \
    X(7, TTOP, 4000) X(8, W0, 1750) X(9, WD, 280) X(10, LEAD, 1) X(11, GATE, 500) X(13, TFIX, 10020) X(14, PACE, 0) X(15, KLAG, KLAGV)
#define X(i, n, v) constexpr int n = v;

struct Scratch {
    uint2 stats[4 * 2048];
    uint2 keys[8 * 128];
    uint2 yp[128 * 56 * 8];
    unsigned epoch[128];
    int ts[128 * 128];
};
__device__ Scratch g_scratch;

struct Maps { CUtensorMap m[5]; };
struct Params {
    const uint4* u; const uint2* logA; const uint2* Aim; const uint2* Cre; const uint2* Cim;
    const uint16_t* logdt; const uint16_t* Dsk; const uint4* wr;
    uint4* out; Scratch* S; uint32_t zero;
};

#define DI __device__ __forceinline__
DI int lane_id() { int l; asm volatile("mov.u32 %0,%%laneid;" : "=r"(l)); __builtin_assume(l >= 0 && l < 32); return l; }
DI int now_ns() { int c; asm volatile("mov.u32 %0,%%globaltimer_lo;" : "=r"(c)::"memory"); return c; }
DI void spin(int t) {
    asm volatile("{.reg .pred p; .reg .s32 c; L: mov.u32 c,%%globaltimer_lo; sub.s32 c,c,%0; setp.lt.s32 p,c,0; @p nanosleep.u32 32; @p bra.uni L;}" ::"r"(t) : "memory");
}
DI void mbar_arrive_e(uint32_t b) { asm volatile("{.reg .pred p; elect.sync _|p,0xffffffff; @p mbarrier.arrive.shared.b64 _,[%0];}" ::"r"(b) : "memory"); }
DI void mbar_expect_e(uint32_t b, int tx) { asm volatile("{.reg .pred p; elect.sync _|p,0xffffffff; @p mbarrier.arrive.expect_tx.shared.b64 _,[%0],%1;}" ::"r"(b), "r"(tx) : "memory"); }
DI void mbar_wait(uint32_t b) {
    asm volatile("{.reg .pred p; W: mbarrier.try_wait.parity.shared.b64 p,[%0],0; @!p bra.uni W; }" ::"r"(b) : "memory");
}
DI void bulk_e(uint32_t dst, const void* src, uint32_t bar, int bytes) {
    asm volatile("{.reg .pred p; elect.sync _|p,0xffffffff; @p cp.async.bulk.shared::cluster.global.mbarrier::complete_tx::bytes [%0],[%1],%3,[%2];}" ::"r"(dst), "l"(src), "r"(bar), "r"(bytes) : "memory");
}
DI void tma3d_e(uint32_t dst, const CUtensorMap* m, int c1, int c2, uint32_t bar) {
    asm volatile("{.reg .pred p; elect.sync _|p,0xffffffff; @p mbarrier.arrive.expect_tx.shared.b64 _,[%2],8192;\n"
                 "@p cp.async.bulk.tensor.3d.shared::cluster.global.mbarrier::complete_tx::bytes [%0],[%1,{0,%3,%4}],[%2];}" ::"r"(dst), "l"(m), "r"(bar), "r"(c1), "r"(c2) : "memory");
}
DI void tma5d_mc_e(uint32_t dst, const CUtensorMap* m, int c0, int c2, uint32_t bar) {
    asm volatile("{.reg .pred p; elect.sync _|p,0xffffffff;\n"
                 "@p cp.async.bulk.tensor.5d.shared::cluster.global.mbarrier::complete_tx::bytes.multicast::cluster [%0],[%1,{%3,0,%4,0,0}],[%2],%5;}"
                 ::"r"(dst), "l"(m), "r"(bar), "r"(c0), "r"(c2), "h"((uint16_t)3) : "memory");
}
DI void tma5d_st_e(uint32_t src, const CUtensorMap* m, int c0, int c2, int c4) {
    asm volatile("{.reg .pred p; elect.sync _|p,0xffffffff; @p cp.async.bulk.tensor.5d.global.shared::cta.bulk_group [%1,{%2,0,%3,0,%4}],[%0];}" ::"r"(src), "l"(m), "r"(c0), "r"(c2), "r"(c4) : "memory");
}
DI void mbar_arrive_peer_e(uint32_t b) { asm volatile("{.reg .pred p; elect.sync _|p,0xffffffff; @p mbarrier.arrive.relaxed.cluster.shared::cluster.b64 _,[%0];}" ::"r"(b) : "memory"); }
DI void st_async(uint32_t dst, const uint4& v, uint32_t bar) {
    asm volatile("st.async.shared::cluster.mbarrier::complete_tx::bytes.v4.b32 [%0],{%1,%2,%3,%4},[%5];" ::"r"(dst), "r"(v.x), "r"(v.y), "r"(v.z), "r"(v.w), "r"(bar) : "memory");
}
DI void fence_async() { asm volatile("fence.proxy.async.shared::cta;" ::: "memory"); }
DI void bar_sync(int id, int n) { asm volatile("bar.sync %0,%1;" ::"r"(id), "r"(n) : "memory"); }
DI void bar_arrive(int id, int n) { asm volatile("bar.arrive %0,%1;" ::"r"(id), "r"(n) : "memory"); }
DI uint4 ldg128(const void* p) { uint4 v; asm volatile("ld.global.nc.v4.u32 {%0,%1,%2,%3},[%4];" : "=r"(v.x), "=r"(v.y), "=r"(v.z), "=r"(v.w) : "l"(p) : "memory"); return v; }
DI uint2 ldg64(const void* p) { uint2 v; asm volatile("ld.global.nc.v2.u32 {%0,%1},[%2];" : "=r"(v.x), "=r"(v.y) : "l"(p) : "memory"); return v; }
DI uint4 ldr128(const void* p) {
    uint4 v;
    asm volatile("{.reg .b128 t; .reg .b64 a,b; ld.relaxed.gpu.global.b128 t,[%4]; mov.b128 {a,b},t; mov.b64 {%0,%1},a; mov.b64 {%2,%3},b;}"
                 : "=r"(v.x), "=r"(v.y), "=r"(v.z), "=r"(v.w) : "l"(p) : "memory");
    return v;
}
DI uint2 ldr64(const void* p) { uint2 v; asm volatile("{.reg .b64 t; ld.relaxed.gpu.global.b64 t,[%2]; mov.b64 {%0,%1},t;}" : "=r"(v.x), "=r"(v.y) : "l"(p) : "memory"); return v; }
DI void str64(void* p, uint32_t x, uint32_t y) { asm volatile("{.reg .b64 t; mov.b64 t,{%1,%2}; st.relaxed.gpu.global.b64 [%0],t;}" ::"l"(p), "r"(x), "r"(y) : "memory"); }
DI uint32_t lds32(uint32_t a) { uint32_t v; asm volatile("ld.shared.u32 %0,[%1];" : "=r"(v) : "r"(a) : "memory"); return v; }
DI uint32_t lds16(uint32_t a) { uint32_t v; asm volatile("ld.shared.u16 %0,[%1];" : "=r"(v) : "r"(a) : "memory"); return v; }
DI uint2 lds64(uint32_t a) { uint2 v; asm volatile("ld.shared.v2.u32 {%0,%1},[%2];" : "=r"(v.x), "=r"(v.y) : "r"(a) : "memory"); return v; }
DI uint4 lds128(uint32_t a) { uint4 v; asm volatile("ld.shared.v4.u32 {%0,%1,%2,%3},[%4];" : "=r"(v.x), "=r"(v.y), "=r"(v.z), "=r"(v.w) : "r"(a) : "memory"); return v; }
DI void sts16(uint32_t a, uint32_t v) { asm volatile("st.shared.u16 [%0],%1;" ::"r"(a), "r"(v) : "memory"); }
DI void sts32(uint32_t a, uint32_t v) { asm volatile("st.shared.u32 [%0],%1;" ::"r"(a), "r"(v) : "memory"); }
DI void sts64(uint32_t a, uint32_t x, uint32_t y) { asm volatile("st.shared.v2.u32 [%0],{%1,%2};" ::"r"(a), "r"(x), "r"(y) : "memory"); }
DI void sts128(uint32_t a, uint32_t x, uint32_t y, uint32_t z, uint32_t w) { asm volatile("st.shared.v4.u32 [%0],{%1,%2,%3,%4};" ::"r"(a), "r"(x), "r"(y), "r"(z), "r"(w) : "memory"); }
DI uint4 ldsm4(uint32_t a) { uint4 v; asm volatile("ldmatrix.sync.aligned.m8n8.x4.shared.b16 {%0,%1,%2,%3},[%4];" : "=r"(v.x), "=r"(v.y), "=r"(v.z), "=r"(v.w) : "r"(a) : "memory"); return v; }
DI uint4 ldsm4t(uint32_t a) { uint4 v; asm volatile("ldmatrix.sync.aligned.m8n8.x4.trans.shared.b16 {%0,%1,%2,%3},[%4];" : "=r"(v.x), "=r"(v.y), "=r"(v.z), "=r"(v.w) : "r"(a) : "memory"); return v; }
DI void stsm4(uint32_t a, uint32_t x, uint32_t y, uint32_t z, uint32_t w) { asm volatile("stmatrix.sync.aligned.m8n8.x4.shared.b16 [%0],{%1,%2,%3,%4};" ::"r"(a), "r"(x), "r"(y), "r"(z), "r"(w) : "memory"); }
DI void stsm4t(uint32_t a, uint32_t x, uint32_t y, uint32_t z, uint32_t w) { asm volatile("stmatrix.sync.aligned.m8n8.x4.trans.shared.b16 [%0],{%1,%2,%3,%4};" ::"r"(a), "r"(x), "r"(y), "r"(z), "r"(w) : "memory"); }
DI void mma_bf(float (&d)[4], uint32_t a0, uint32_t a1, uint32_t a2, uint32_t a3, uint32_t b0, uint32_t b1) {
    asm("mma.sync.aligned.m16n8k16.row.col.f32.bf16.bf16.f32 {%0,%1,%2,%3},{%4,%5,%6,%7},{%8,%9},{%0,%1,%2,%3};"
        : "+f"(d[0]), "+f"(d[1]), "+f"(d[2]), "+f"(d[3]) : "r"(a0), "r"(a1), "r"(a2), "r"(a3), "r"(b0), "r"(b1));
}
DI void mma_bf(float (&d)[4], const uint4& a, uint32_t b0, uint32_t b1) { mma_bf(d, a.x, a.y, a.z, a.w, b0, b1); }
typedef uint32_t h4[2];
DI void mma_h(h4& d, const uint4& a, uint32_t b0, uint32_t b1) {
    asm("mma.sync.aligned.m16n8k16.row.col.f16.f16.f16.f16 {%0,%1},{%2,%3,%4,%5},{%6,%7},{%0,%1};"
        : "+r"(d[0]), "+r"(d[1]) : "r"(a.x), "r"(a.y), "r"(a.z), "r"(a.w), "r"(b0), "r"(b1));
}
DI void mma_k8(h4& d, uint32_t a0, uint32_t a1, uint32_t b0) {
    asm("mma.sync.aligned.m16n8k8.row.col.f16.f16.f16.f16 {%0,%1},{%2,%3},{%4},{%0,%1};" : "+r"(d[0]), "+r"(d[1]) : "r"(a0), "r"(a1), "r"(b0));
}
DI void mma_cvt(float (&d)[4], const h4& a, uint32_t b) {
    asm("mma.sync.aligned.m16n8k8.row.col.f32.f16.f16.f32 {%0,%1,%2,%3},{%4,%5},{%6},{%7,%7,%7,%7};"
        : "=f"(d[0]), "=f"(d[1]), "=f"(d[2]), "=f"(d[3]) : "r"(a[0]), "r"(a[1]), "r"(b), "f"(0.f));
}
DI uint32_t pk_bf(float lo, float hi) { uint32_t r; asm("cvt.rn.bf16x2.f32 %0,%1,%2;" : "=r"(r) : "f"(hi), "f"(lo)); return r; }
DI uint32_t pk_h(float lo, float hi) { uint32_t r; asm("cvt.rn.f16x2.f32 %0,%1,%2;" : "=r"(r) : "f"(hi), "f"(lo)); return r; }
DI float bf_lo(uint32_t v) { return __uint_as_float(v << 16); }
DI float bf_hi(uint32_t v) { return __uint_as_float(v & 0xffff0000u); }
DI float bfr(float x) { return bf_lo(pk_bf(x, 0.f)); }
DI uint32_t hadd(uint32_t a, uint32_t b) { uint32_t r; asm("add.rn.f16x2 %0,%1,%2;" : "=r"(r) : "r"(a), "r"(b)); return r; }
DI uint32_t hsub(uint32_t a, uint32_t b) { uint32_t r; asm volatile("sub.rn.f16x2 %0,%1,%2;" : "=r"(r) : "r"(a), "r"(b)); return r; }
DI uint32_t hscl(uint32_t a) { uint32_t r; asm("mul.rn.f16x2 %0,%1,%2;" : "=r"(r) : "r"(a), "r"(0x01000100)); return r; }
DI uint32_t bsub_lo(uint32_t x, uint32_t m) { uint32_t r; asm("{.reg .b16 l,h; .reg .b32 t; mov.b32 {l,h},%2; mov.b32 t,{l,l}; sub.rn.bf16x2 %0,%1,t;}" : "=r"(r) : "r"(x), "r"(m)); return r; }
DI uint32_t bmul(uint32_t a, uint32_t b) { uint32_t r; asm("mul.rn.bf16x2 %0,%1,%2;" : "=r"(r) : "r"(a), "r"(b)); return r; }
DI uint32_t bfma(uint32_t a, uint32_t b, uint32_t c) { uint32_t r; asm("fma.rn.bf16x2 %0,%1,%2,%3;" : "=r"(r) : "r"(a), "r"(b), "r"(c)); return r; }
DI float ex2(float x) { float r; asm("ex2.approx.ftz.f32 %0,%1;" : "=f"(r) : "f"(x)); return r; }
DI float rcp(float x) { float r; asm("rcp.approx.ftz.f32 %0,%1;" : "=f"(r) : "f"(x)); return r; }
DI float ftanh(float x) { float r; asm("tanh.approx.f32 %0,%1;" : "=f"(r) : "f"(x)); return r; }
DI float fsqrt(float x) { float r; asm("sqrt.approx.ftz.f32 %0,%1;" : "=f"(r) : "f"(x)); return r; }
constexpr float LOG2E = 1.4426950408889634f;
DI float sigm(float x) { return rcp(1.f + ex2(-LOG2E * x)); }
DI float silu(float x) { return x * sigm(x); }
struct cf { float r, i; };
DI cf cmul(cf a, cf b) { return {fmaf(a.r, b.r, -a.i * b.i), fmaf(a.r, b.i, a.i * b.r)}; }
DI float mul2(float a, float b) { float r; asm("{.reg .f32 t; mul.f32 t,%1,%2; mul.f32 %0,t,0f40000000;}" : "=f"(r) : "f"(a), "f"(b)); return r; }
DI cf csq(cf a) { return {fmaf(a.r, a.r, -a.i * a.i), mul2(a.r, a.i)}; }
DI cf csqc(cf a) { return {fmaf(a.r, a.r, -a.i * a.i), mul2(a.r, -a.i)}; }
DI cf cexp(float a2, float be, float p) { float m = ex2(a2 * p); float t = be * p; return {m * __cosf(t), m * __sinf(t)}; }

struct ch2 { uint32_t r, i; };
template <int V>
DI ch2 hmul(ch2 a, uint32_t fr, uint32_t fi) {
    ch2 o;
    if (V) asm("{.reg .b32 t,u; mul.rn.f16x2 t,%3,%5; neg.f16x2 t,t; mul.rn.f16x2 u,%2,%5; fma.rn.f16x2 %0,%2,%4,t; fma.rn.f16x2 %1,%3,%4,u;}"
               : "=&r"(o.r), "=r"(o.i) : "r"(a.r), "r"(a.i), "r"(fr), "r"(fi));
    else asm("{.reg .b32 t,u,n; mul.rn.f16x2 t,%2,%4; mul.rn.f16x2 u,%3,%4; neg.f16x2 n,%3; fma.rn.f16x2 %0,n,%5,t; fma.rn.f16x2 %1,%2,%5,u;}"
             : "=&r"(o.r), "=r"(o.i) : "r"(a.r), "r"(a.i), "r"(fr), "r"(fi));
    return o;
}
DI ch2 hmul(ch2 a, uint32_t f) {
    ch2 o;
    asm("{.reg .b32 t,u,x,y; .reg .b16 l,h; mov.b32 {l,h},%4; mov.b32 x,{l,l}; mov.b32 y,{h,h};\n"
        "mul.rn.f16x2 t,%3,y; neg.f16x2 t,t; fma.rn.f16x2 %0,%2,x,t; mul.rn.f16x2 u,%3,x; fma.rn.f16x2 %1,%2,y,u;}"
        : "=&r"(o.r), "=r"(o.i) : "r"(a.r), "r"(a.i), "r"(f));
    return o;
}
DI uint32_t pk_h(cf f) { return pk_h(f.r, f.i); }
DI void sts_ch2(uint32_t a, ch2 x, ch2 y, ch2 z, ch2 w) { sts128(a, x.r, y.r, z.r, w.r); sts128(a + 512, x.i, y.i, z.i, w.i); }

#define TDUMP
#define TS(i)
#define TV(i, v)
#define T2S(i)

DI void sched_fence(uint32_t Z) { if (FSB == 2) { asm volatile("griddepcontrol.launch_dependents;" ::: "memory"); return; } asm volatile("{.reg .pred p; setp.ne.u32 p,%0,0; @p griddepcontrol.launch_dependents;}" ::"r"(Z) : "memory"); }
DI uint32_t copy(uint32_t v, uint32_t Z) { uint32_t r; asm volatile("xor.b32 %0,%1,%2;" : "=r"(r) : "r"(v), "r"(Z)); return r; }
DI void pin4(uint32_t& a, uint32_t& b, uint32_t& c, uint32_t& d, uint32_t Z) {
    asm volatile("{.reg .pred p; setp.ne.u32 p,%4,0; @p ld.shared.v4.u32 {%0,%1,%2,%3},[%4];}" : "+r"(a), "+r"(b), "+r"(c), "+r"(d) : "r"(Z) : "memory");
}

#define BFRAG(B, s) ((s) & 1) ? B[(s) >> 1].z : B[(s) >> 1].x, ((s) & 1) ? B[(s) >> 1].w : B[(s) >> 1].y
DI uint32_t comp(const uint4& v, int k) { return k == 0 ? v.x : k == 1 ? v.y : k == 2 ? v.z : v.w; }
template <bool FIRST>
DI void conv_half(h4 (&acc)[16], uint32_t aA, uint32_t aB, uint32_t bar, uint32_t Z) {
    constexpr int O = FIRST ? 0 : 8, NT = FIRST ? 5 : 4;
    uint4 A[4], S[2], B[4] = {}, A32, A64, Y;
    h4 P[4], m1[5] = {};
    auto refill = [&](int k, int j) {
        const uint32_t a = aA + j * 32 + k * 512;
        A[2 * k].y = j < 7 ? copy(A[2 * k].z, Z) : lds32(a + 16); A[2 * k].x = lds32(a); A[2 * k].z = lds32(a - 16);
        A[2 * k + 1].w = j < 7 ? copy(A[2 * k + 1].x, Z) : lds32(a + 272); A[2 * k + 1].y = lds32(a + 256); A[2 * k + 1].x = lds32(a + 240);
    };
    auto diff = [&](int k, int j) {
        uint4 &a = A[2 * k], &c = A[2 * k + 1];
        a.w = copy(a.x, Z); c.z = copy(c.y, Z);
        S[k].y = j < 7 ? copy(S[k].z, Z) : hsub(a.y, c.w); S[k].z = hsub(a.z, c.x); S[k].x = hsub(a.x, c.y); S[k].w = hsub(a.w, c.z);
    };
    auto pre = [&](int s) { P[s][0] = hsub(B[s].w, B[s].x); P[s][1] = hsub(B[s].z, B[s].y); };
    auto extra = [&](int j, int t, uint32_t b0, uint32_t b1) {
        if (j == 1 && O + t + 4 < 16) mma_k8(acc[O + t + 4], Y.x, Y.y, b1);
        if (j == 1 && FIRST) mma_k8(acc[t + 8], Y.z, Y.w, b1);
        if (j == 0 && O + t + 4 < 16) mma_h(acc[O + t + 4], A32, b0, b1);
        if (j == 0 && FIRST) mma_h(acc[t + 8], A64, b0, b1);
    };
    refill(0, 7); refill(1, 7);
    if (!FIRST)
#pragma unroll
        for (int k = 0; k < 2 * NT; k++) acc[O + (k | 1)][k & 1] = hsub(acc[O + (k | 1)][k & 1], acc[O + (k & ~1)][k & 1]);
    diff(0, 7);
    if (FIRST) { pin4(A[0].x, A[0].y, A[0].z, A[0].w, Z); pin4(A[1].x, A[1].y, A[1].z, A[1].w, Z); pin4(S[0].x, S[0].y, S[0].z, S[0].w, Z); }
    mbar_wait(bar);
#pragma unroll
    for (int i = 0; i < 4; i++) B[i] = ldsm4(aB - 7 * BS + i * 2 * TS8);
#pragma unroll
    for (int j = 7; j >= 0; j--) {
        if (j == 2) { Y.x = lds32(aA + 1040); Y.y = Y.x & Z; if (FIRST) { Y.z = lds32(aA + 1104); Y.w = Y.z & Z; } }
#pragma unroll
        for (int s = 0; s < 4; s++) {
            if (s) pre(s - 1);
            if (s == 2) diff(1, j);
            mma_h(acc[O + 2 * s], A[0], B[s].x, B[s].y); mma_h(m1[s], A[1], B[s].z, B[s].w);
            if (FM >> s & 1) sched_fence(Z);
        }
        pre(3);
        if (j) refill(0, j - 1);
        if (j == 0) {
            A32.x = lds32(aA + 1024); A32.y = copy(Y.x, Z); A32.z = lds32(aA + 1008); A32.w = copy(A32.x, Z);
            if (FIRST) { A64.x = lds32(aA + 1088); A64.y = copy(Y.z, Z); A64.z = copy(Y.w, Z); A64.w = copy(A64.x, Z); }
        }
#pragma unroll
        for (int s = 0; s < 4; s++) {
            if (s + 1 < NT) { mma_h(acc[O + 2 * s + 2], A[2], B[s].x, B[s].y); mma_h(m1[s + 1], A[3], B[s].z, B[s].w); }
            if (j) extra(j, 2 * s, B[s].x, B[s].y);
            if (j) { if (s + 1 < NT && (FM >> (4 + s + !FIRST) & 1)) sched_fence(Z); B[s] = ldsm4(aB - (j - 1) * BS + s * 2 * TS8); }
        }
        if (j) refill(1, j - 1);
#pragma unroll
        for (int s = 0; s < 4; s++) mma_h(acc[O + 2 * ((s + !FIRST) & 3) + 1], S[0], P[(s + !FIRST) & 3][0], P[(s + !FIRST) & 3][1]);
        if (j) { if (FM >> 8 & 1) sched_fence(Z); diff(0, j - 1); }
        if (FIRST) mma_h(acc[9], S[1], P[3][0], P[3][1]);
#pragma unroll
        for (int s = 0; s < 3; s++) mma_h(acc[O + 2 * s + 3], S[1], P[s][0], P[s][1]);
#pragma unroll
        for (int s = 3; s >= 0; s--) { if (!j) extra(j, 2 * s, B[s].x, B[s].y); extra(j, 2 * s + 1, P[s][0], P[s][1]); }
        if (j && (FM >> 9 & 1)) sched_fence(Z);
    }
#pragma unroll
    for (int k = 0; k < 16 - O; k++) {
        const uint32_t e = acc[O + (k & ~1)][k & 1];
        acc[O + (k | 1)][k & 1] = hadd(k < 2 * NT ? hadd(e, m1[k >> 1][k & 1]) : e, acc[O + (k | 1)][k & 1]);
    }
#pragma unroll
    for (int k = 0; k < (FIRST ? 10 : 6); k++) acc[O + 2 + (k & ~1)][k & 1] = hadd(acc[O + 2 + (k & ~1)][k & 1], m1[k >> 1][k & 1]);
}

__global__ void __cluster_dims__(2, 1, 1) __launch_bounds__(640, 1)
fused_kernel(const __grid_constant__ Params prm, const __grid_constant__ Maps maps) {
    const CUtensorMap &mg = maps.m[0], &md = maps.m[2], &mx = maps.m[3], &mo = maps.m[4];
    extern __shared__ __align__(1024) unsigned char smem_raw[];
    SCHED(X)
    const uint32_t tid = threadIdx.x;
    uint2 vA, vI, vR, vC;
    uint32_t ldt, Dsk;
    if (tid < 256) {
        const int e = blockIdx.x * 256 + tid;
        asm volatile("ld.global.nc.u16 %0,[%1];" : "=r"(ldt) : "l"(prm.logdt + (e >> 5)) : "memory");
        asm volatile("ld.global.nc.u16 %0,[%1];" : "=r"(Dsk) : "l"(prm.Dsk + (e >> 5)) : "memory");
        vA = ldg64(prm.logA + e); vI = ldg64(prm.Aim + e); vR = ldg64(prm.Cre + e); vC = ldg64(prm.Cim + e);
    }
    const int t0 = __shfl_sync(~0u, now_ns() + (threadIdx.x >> 10), 0);
    uint32_t sb = (uint32_t)__cvta_generic_to_shared(smem_raw);
    if (SBC) sb = __shfl_sync(~0u, sb + (threadIdx.x >> 10), 0);
    const int b = blockIdx.x, rk = b & 1, q = b >> 1;
    const int w = __shfl_sync(~0u, tid >> 5, 0);
#define LANES const int lane = lane_id(), g = lane >> 2, c = lane & 3, mi = lane >> 3, r8 = lane & 7; (void)g; (void)c; (void)mi; (void)r8
    uint32_t pb;
    asm("mapa.shared::cluster.u32 %0,%1,%2;" : "=r"(pb) : "r"(sb), "r"(rk ^ 1));
    if (w < 17) asm volatile("barrier.cluster.arrive.relaxed.aligned;" ::: "memory");
    const uint32_t Z = prm.zero;

    if (w < 8) {
        LANES;
        const uint32_t pv = sb + O_PRIV + w * PRIV, tb = pv + P_TAB, rw = sb + O_RAW + w * 32;
        const uint32_t dd = g - 2 * c;
        uint32_t st = pv + lane * 16, cyP = pv + 528 + c * 1056 + mi * 4, Zr = Z;
        uint32_t a1 = tb + ((dd + 14) & 4) * (PB / 4) + ((dd + 14) >> 3) * 16 + ((dd + 14) & 3) * 4, t2 = tb + T2 + dd * 8;
        uint32_t aB = rw + r8 * BS + (mi >> 1) * TS8 + ((mi ^ mi >> 1) & 1) * 16, ac0 = rw + lane * BS;
        uint32_t fa = pv + 16 + r8 * 16 + mi * 528, fb = fa + ((mi & 1) ? -528 : 512), fc = (mi < 2 ? fa : fb) + 4 * 528;
        uint32_t Id = (dd >> 1) ? 0 : 0x3c00 << (16 * (g & 1)), kt = pv + (mi * 8 + (r8 >> 1) + (r8 & 1) * 4) * 16;
        uint32_t w2 = tb + T2 + (lane & 1) * 320 + (lane >> 1) * 8, w3 = tb + T3 + lane * 4;
        sts64(rw - TS8 + g * BS + c * 8, 0, 0);
        sts128(tb + (mi & 1) * PB + (r8 < 2 ? r8 : r8 + 64) * 16, 0, 0, 0, 0);
        h4 kd[6] = {};
        uint32_t lA = pv + (mi >> 1) * 512 + (mi & 1) * 128 + r8 * 16, lB = pv + (2 + mi) * 512 + r8 * 16;
        uint32_t lC = pv + (6 + (mi & 1)) * 512 + (mi >> 1) * 128 + r8 * 16, lF = pv + 4096 + (mi & 1) * 64 + (mi >> 1) * 16;
        uint32_t sF = pv + 4096 + lane * 2, j0 = 0;
        pin4(a1, t2, aB, ac0, Z); pin4(fa, fb, fc, cyP, Z); pin4(st, Zr, Id, kt, Z); pin4(lA, lB, lC, lF, Z); pin4(sF, w2, w3, j0, Z);
        sched_fence(Z);
        if (!LATE) asm volatile("setmaxnreg.inc.sync.aligned.u32 %0;" ::"n"(RM));
        const float dt = bfr(ex2(bf_lo(ldt + (lane & Z)) * LOG2E));
        uint32_t mx2 = __vmaxu2(__vmaxu2(vR.x & 0x7fff7fffu, vR.y & 0x7fff7fffu), __vmaxu2(vC.x & 0x7fff7fffu, vC.y & 0x7fff7fffu));
        const int ex = min(max(max((int)((__reduce_max_sync(~0u, max(mx2 >> 16, mx2 & 0xffffu)) >> 7) + (__float_as_uint(dt) >> 23)), (int)((Dsk >> 7) & 255) + 109), 140), 369);
        const float cs = dt * __uint_as_float((387 - ex) << 23), dl = -dt * LOG2E, ncs = __uint_as_float(__float_as_uint(cs) ^ 0x80000000u ^ Z);
        TS(88 + w); T2S(0);
        auto gen = [&](uint32_t sel) {
            const float a2 = bfr(ex2(__uint_as_float(__byte_perm(vA.x, vA.y, sel) & 0xffff0000u) * LOG2E)) * dl;
            const float be = __uint_as_float(__byte_perm(vI.x, vI.y, sel) & 0xffff0000u) * dt;
            const cf wv = {__uint_as_float(__byte_perm(vR.x, vR.y, sel) & 0xffff0000u) * cs, __uint_as_float(__byte_perm(vC.x, vC.y, sel) & 0xffff0000u) * ncs};
            const cf y1 = cexp(a2, -be, 1.f), y2 = csq(y1), y4 = csq(y2), z8 = csqc(y4), z16 = csq(z8), z32 = csq(z16);
            const cf z64 = cexp(a2, be, 64.f);
            {
                const uint32_t f = pk_h(z64) ^ Z, f16 = pk_h(z16);
                const ch2 m0 = {pk_h(1.f, z32.r), pk_h(0.f, z32.i)}, m1 = hmul(m0, pk_h(z8));
                sts_ch2(st, m0, m1, hmul(m0, f16), hmul(m1, f16));
                sts16(sF, f); sts16(sF + 64, f >> 16);
            }
            if (KV & 4) sched_fence(Z);
            {
                const cf w4 = cmul(wv, y4), y256 = csqc(csq(z64)), y512 = csq(y256);
                const uint32_t f2 = pk_h(y2), f256 = pk_h(y256), f512 = pk_h(y512);
                const ch2 p0 = {pk_h(wv.r, w4.r), pk_h(wv.i, w4.i)};
                const ch2 p1 = hmul(p0, pk_h(y1)), p2 = hmul(p0, f2), p4 = hmul(p0, pk_h(y4));
                sts_ch2(st + 1024, p1, p2, hmul(p1, f2), p4);
                if (KV & 8) sched_fence(Z);
                const ch2 e1 = hmul(p4, f256);
                sts_ch2(st + 2048, hmul(p2, f256), e1, hmul(p4, f512), hmul(e1, f512));
                const ch2 g0 = {__byte_perm(p4.r, e1.r, 0x7632), __byte_perm(p4.i, e1.i, 0x7632)}, s0 = hmul(g0, pk_h(csq(y512)));
                sts_ch2(st + 3072, s0, hmul(s0, f512), p0, g0);
            }
            __syncwarp();
        };
        auto mul = [&]() {
#pragma unroll
            for (int k2 = 0; k2 < 2; k2++) {
                const uint4 M = ldsm4t(lA + k2 * 256), F = ldsm4(lF + k2 * 32);
                uint4 B[3];
                B[0] = ldsm4t(lB + k2 * 256); B[1] = ldsm4t(lB + k2 * 256 + 128); B[2] = ldsm4t(lC + k2 * 256);
#pragma unroll
                for (int i = 1; i >= 0; i--) {
                    const uint32_t fr = i ? F.z : F.x, fi = i ? F.w : F.y;
                    const ch2 m0 = {i ? M.y ^ Z : (KV & 1) ? M.x ^ Z : M.x, i ? M.w ^ Z : (KV & 1) ? M.z ^ Z : M.z}, m1 = hmul<1>(m0, fr, fi), m2 = hmul<0>(m1, fr, fi), m3 = hmul<1>(m2, fr, fi);
                    const uint4 A0 = make_uint4(m0.r, m1.r, m0.i, m1.i), A1 = make_uint4(m2.r, m3.r, m2.i, m3.i);
                    if (KV & 2) sched_fence(Z);
                    mma_h(kd[0], A0, B[i].x, B[i].y); mma_h(kd[1], A0, B[i].z, B[i].w); mma_h(kd[2], A0, i ? B[2].z : B[2].x, i ? B[2].w : B[2].y);
                    mma_h(kd[3], A1, B[i].x, B[i].y); mma_h(kd[4], A1, B[i].z, B[i].w); mma_h(kd[5], A1, i ? B[2].z : B[2].x, i ? B[2].w : B[2].y);
                }
            }
            __syncwarp();
        };
        if (w >= 4 && KLAG) spin(t0 + KLAG);
        gen(0x1044);
        if (LATE) asm volatile("setmaxnreg.inc.sync.aligned.u32 %0;" ::"n"(RM));
        bar_sync(w < 7 ? 9 + w : 6, 64);
#pragma unroll 1
        for (uint32_t sel = 0x3244; sel < 0x8000; sel += 0x2200) {
            mul();
            gen(sel);
        }
        mul();
        TS(w == 0 ? 59 : w == 4 ? 60 : 63); T2S(1);
        {
#pragma unroll
            for (int nt = 0; nt < 3; nt++) stsm4(kt + nt * 512, kd[nt][0], kd[nt][1], kd[nt + 3][0], kd[nt + 3][1]);
            __syncwarp();
            uint4 R0 = lds128(st), R1 = lds128(st + 512), R2 = lds128(st + 1024);
            R0.x = hscl(R0.x); R0.y = hscl(R0.y); R0.z = hscl(R0.z); R0.w = hscl(R0.w);
            R1.x = hscl(R1.x); R1.y = hscl(R1.y); R1.z = hscl(R1.z); R1.w = hscl(R1.w);
            R2.x = hscl(R2.x); R2.y = hscl(R2.y); R2.z = hadd(hscl(R2.z), pk_h(bf_lo(Dsk) * __uint_as_float((370 - ex) << 23), 0.f));
            const bool l31 = lane == 31, l2 = lane < 2;
            uint32_t nx = __shfl_down_sync(~0u, R0.x, 1);
            if (l31) nx = R0.w >> 16;
            const uint32_t pr = __shfl_sync(~0u, l31 ? R0.w : R1.y, lane - 1);
            const uint32_t sA = __shfl_sync(~0u, R1.z, lane - 2), sB = __shfl_sync(~0u, R1.w, lane - 2);
            const uint32_t s0 = __shfl_sync(~0u, R2.x, lane - 2), s1 = __shfl_sync(~0u, R2.y, lane - 2);
            sts128(st + P_TAB + 32, __byte_perm(R0.y, R0.x, 0x5410), __byte_perm(R0.z, R0.y, 0x5410), __byte_perm(R0.w, R0.z, 0x5410), __byte_perm(R0.x, R0.w, 0x5432));
            sts128(st + P_TAB + PB + 32, __byte_perm(R0.y, R0.x, 0x7632), __byte_perm(R0.z, R0.y, 0x7632), __byte_perm(R0.w, R0.z, 0x7632), __byte_perm(R0.w, nx, 0x3254));
            const uint32_t d1 = __byte_perm(R1.y, 0, 0x1010), d3 = __byte_perm(R1.y, 0, 0x3232);
            sts128(st + P_TAB + 544, __byte_perm(pr, R1.x, 0x3254), __byte_perm(R1.y, R1.x, 0x5410), d1, d1);
            sts128(st + P_TAB + PB + 544, __byte_perm(R1.x, R1.y, 0x5432), __byte_perm(R1.y, R1.x, 0x7632), d3, d3);
            uint32_t a = w2;
            const uint32_t pA = l2 ? 0 : sA, pB = l2 ? sA : sB, pT = l2 ? sB : 0;
            sts64(a, __byte_perm(R1.z, pA, 0x5410), __byte_perm(R1.z, pA, 0x7632));
            sts64(a + 128, __byte_perm(R1.w, pB, 0x5410), __byte_perm(R1.w, pB, 0x7632));
            if (lane < 16) sts64(a + 256, pT << 16, pT & 0xffff0000u);
            a = w3;
            const uint32_t p0 = __byte_perm(0, s0, l2 ? 0x5432 : 0x7654), p1 = __byte_perm(s0, s1, l2 ? 0x5432 : 0x7654);
            sts32(a, __byte_perm(R2.x, p0, 0x5410)); sts32(a + 128, __byte_perm(R2.x, p0, 0x7632));
            sts32(a + 256, __byte_perm(R2.y, p1, 0x5410)); sts32(a + 384, __byte_perm(R2.y, p1, 0x7632));
            if (lane == 0) sts64(st + P_TAB + PB + 24, R2.z & 0xffffu, __byte_perm(R0.x, R2.z, 0x5410));
            if (l31) {
                sts64(st + P_TAB + 35 * 16, d3, d3 << 16);
                sts128(st + P_TAB + 39 * 16, 0, R1.w >> 16, __byte_perm(R1.w, 0, 0x3232), R1.w & 0xffff0000u);
            }
        }
        __syncwarp();
        TS(1); T2S(9);
        h4 acc[16] = {};
        const uint32_t t3 = t2 + T3 - T2, fo = st + 16, sc = (ex - 115) * 0x800080;
        auto put_tiles = [&](int i0, int i1, int bar) {
#pragma unroll
            for (int i = i0; i < i1; i++) {
                float d[4], e[4];
                mma_cvt(d, acc[2 * i], Id);
                mma_cvt(e, acc[2 * i + 1], Id);
                stsm4t(aB + (2 * i - 1) * TS8, bmul(pk_bf(d[0], d[1]), sc), bmul(pk_bf(d[2], d[3]), sc), bmul(pk_bf(e[2], e[3]), sc), bmul(pk_bf(e[0], e[1]), sc));
            }
            __syncwarp();
            mbar_arrive_e(sb + B_Y + bar * 8);
        };
        uint32_t U[13], cy;
        auto fetch = [&](int p) {
            const uint32_t ac = ac0 + p * 4 * TS8;
            const uint4 q2 = lds128(ac), q3 = lds128(ac + 16);
            cy = p ? lds32(cyP + 512) : 0;
            const uint2 q0 = lds64(ac - BS + 8);
            const uint4 q1 = lds128(ac - BS + 16);
            U[0] = q0.x; U[1] = q0.y; U[2] = q1.x; U[3] = q1.y; U[4] = q1.z; U[5] = q1.w; U[6] = q2.x; U[7] = q2.y; U[8] = q2.z; U[9] = q2.w;
            U[10] = q3.x; U[11] = q3.y; U[12] = q3.z;
            __syncwarp();
        };
        auto filter = [&](int p) {
            if (p < 2 || c < 2) sts32(cyP, cy);
            uint32_t Q[13], Pp[12], P4[12], C3[12], C5[10];
#pragma unroll
            for (int k = 1; k < 13; k++) Q[k] = __byte_perm(U[k - 1], U[k], 0x5432);
#pragma unroll
            for (int k = 1; k < 12; k++) Pp[k] = hadd(U[k], Q[k]);
#pragma unroll
            for (int k = 2; k < 12; k++) P4[k] = hadd(Pp[k], Pp[k - 1]);
#pragma unroll
            for (int k = 3; k < 12; k++) C3[k] = hadd(Pp[k], Q[k + 1]);
#pragma unroll
            for (int k = 1; k < 10; k++) C5[k] = hadd(P4[k + 1], U[k - 1]);
            if (p < 2)
#pragma unroll
                for (int h = 0; h < 2; h++) {
                    const int k = 2 + 4 * h;
                    sts128(fo + (4 + h) * 528, hadd(P4[k], C3[k + 1]), hadd(P4[k + 1], C3[k + 2]), hadd(P4[k + 2], C3[k + 3]), hadd(P4[k + 3], C3[k + 4]));
                    sts128(fo + (6 + h) * 528, hadd(P4[k + 2], C5[k - 1]), hadd(P4[k + 3], C5[k]), hadd(P4[k + 4], C5[k + 1]), hadd(P4[k + 5], C5[k + 2]));
                }
            sts128(fo, C3[4], C3[5], C3[6], C3[7]); sts128(fo + 528, C3[8], C3[9], C3[10], C3[11]);
            sts128(fo + 2 * 528, C5[2], C5[3], C5[4], C5[5]); sts128(fo + 3 * 528, C5[6], C5[7], C5[8], C5[9]);
            __syncwarp();
        };
        uint2 T[5], U2[5], V[8];
        uint4 Fa[4], Fb[4], Fc[4];
        auto taps = [&](int nv) {
#pragma unroll
            for (int D = 0; D < 5; D++) { T[D] = lds64(t2 + D * 64); U2[D] = lds64(t2 + 320 + D * 64); }
#pragma unroll
            for (int D = 0; D < nv; D++) V[D] = lds64(t3 + D * 64);
        };
        auto coarse = [&](int p, int t0, int t1, int lv) {
#pragma unroll
            for (int gl = 0; gl < 4; gl++) {
#pragma unroll
                for (int t = t0; t < t1; t++) { const int D = t - 4 * p - gl - 4; if ((lv & 1) && D >= 0 && D < 5) mma_h(acc[t], Fa[gl], T[D].x, T[D].y); }
#pragma unroll
                for (int t = t0; t < t1; t++) { const int D = t - 4 * p - gl - 4; if ((lv & 2) && D >= 0 && D < 5) mma_h(acc[t], Fb[gl], U2[D].x, U2[D].y); }
#pragma unroll
                for (int t = t1 - 1; t >= t0; t--) { const int D = t - 4 * p - gl - 8; if ((lv & 4) && D >= 0) mma_h(acc[t], Fc[gl], V[D].x, V[D].y); }
            }
        };
        auto frags = [&](int lv) {
#pragma unroll
            for (int gl = 0; gl < 4; gl++) {
                if (lv & 1) Fa[gl] = ldsm4t(fa + gl * 128);
                if (lv & 2) Fb[gl] = ldsm4t(fb + gl * 128);
                if (lv & 4) Fc[gl] = ldsm4t(fc + gl * 128);
            }
        };
        T2S(10);
        conv_half<true>(acc, a1, aB, sb + B_RAW, Zr);
        T2S(11);
        fetch(0);
        put_tiles(0, 2, 0);
        filter(0);
        taps(8);
        frags(1); coarse(0, 4, 16, 1);
        frags(6); coarse(0, 4, 16, 6);
        fetch(1);
        put_tiles(2, 4, 1);
        filter(1);
        if (!ORD) { frags(1); coarse(1, 8, 16, 1); frags(6); coarse(1, 8, 16, 6); }
        T2S(22);
        conv_half<false>(acc, a1, aB + 8 * TS8, sb + B_RAW + 8, Zr);
        T2S(23);
        if (PSY & 2) bar_sync(9 + (w & 3), 64);
        if (ORD) {
            taps(0);
            frags(3);
            fetch(2);
            coarse(1, 8, PSY & 1 ? 12 : 16, 3);
            put_tiles(4, 6, 2);
            if (PSY & 1) { bar_sync(9 + (w & 3), 64); coarse(1, 12, 16, 3); }
            filter(2);
#pragma unroll
            for (int D = 0; D < 4; D++) V[D] = lds64(t3 + D * 64);
            frags(7);
            coarse(1, 12, 16, 4);
            coarse(2, 12, ORD == 1 ? 14 : 16, 3);
            put_tiles(6, 7, 3);
            if (ORD == 1) {
                if (PSY & 4) bar_sync(9 + (w & 3), 64); else sched_fence(Zr);
                h4 e[2] = {};
#pragma unroll
                for (int gl = 0; gl < 4; gl++)
#pragma unroll
                    for (int t = 1; t >= 0; t--)
                        if (t + 2 - gl >= 0) { mma_h(acc[14 + t], Fa[gl], T[t + 2 - gl].x, T[t + 2 - gl].y); mma_h(e[t], Fb[gl], U2[t + 2 - gl].x, U2[t + 2 - gl].y); }
#pragma unroll
                for (int k = 0; k < 4; k++) acc[14 + (k >> 1)][k & 1] = hadd(acc[14 + (k >> 1)][k & 1], e[k >> 1][k & 1]);
            }
        } else {
            fetch(2);
            put_tiles(4, 6, 2);
            filter(2);
            taps(0);
            frags(3); coarse(2, 12, 16, 3);
            put_tiles(6, 7, 3);
        }
        put_tiles(7, 8, 4);
        T2S(24);
        TS(3);
        TDUMP;
    } else if (w < 16) {
        LANES;
        const int hw = w - 8;
        if (RH < 96) asm volatile("setmaxnreg.dec.sync.aligned.u32 %0;" ::"n"(RH));
        if (RH > 96) asm volatile("setmaxnreg.inc.sync.aligned.u32 %0;" ::"n"(RH));
        uint32_t tag;
        asm volatile("ld.relaxed.gpu.global.u32 %0,[%1];" : "=r"(tag) : "l"(prm.S->epoch + b) : "memory");
        tag = ~tag << 31;
        {
            uint32_t W[16];
#pragma unroll
            for (int k = 0; k < 4; k++) {
                const uint4 v = ldg128(prm.wr + hw * 16 + (k ^ (g & 1)) * 4 + c);
                W[4 * k] = v.x; W[4 * k + 1] = v.y; W[4 * k + 2] = v.z; W[4 * k + 3] = v.w;
            }
#pragma unroll
            for (int k = 0; k < 16; k++) if (g & 2) W[k] = 0x3f803f80u;
            const bool dg = mi == c, od = g & 1;
            uint32_t ra = sb + O_ROWS + g * 2048 + hw * 256 + od * 64 + c * 16;
            uint32_t pa = sb + O_PST + ((dg ? 0 : 8 + 4 * (g & 2)) + 2 * c + od) * 48 + hw * 4;
            TS(hw == 4 ? 22 : 63);
            bar_sync(3, 288);
#pragma unroll 1
            for (int hf = 0; hf < 2; hf++) {
                float d[4] = {}, e[4] = {};
                mbar_wait(sb + B_ROW + hf * 8);
                TS(hw == 4 ? (hf ? 23 : 58) : 63);
#pragma unroll
                for (int k = 0; k < 4; k++) {
                    const uint4 x = lds128((ra ^ ((k & 1) << 6)) + (k >> 1) * 128);
                    mma_bf(d, x.x ^ Z, W[4 * k], x.y ^ Z, W[4 * k + 1], x.x, x.y);
                    mma_bf(e, x.z ^ Z, W[4 * k + 2], x.w ^ Z, W[4 * k + 3], x.z, x.w);
                }
#define PICK2(e) (dg ? (od ? e[1] : e[0]) : (od ? e[3] : e[2]))
                sts32(pa, __float_as_uint(PICK2(d) + PICK2(e)));
                TS(hf ? 63 : 8 + hw);
                bar_arrive(1 + 3 * hf, 288);
                ra += 16384; pa += 1152;
            }
        }
        const int n0 = hw + (hw & 4);
        const uint32_t tok = n0 * 16 + (lane & 2) * 32 + (lane & 1) * 8 + g, xo = O_XT + lane * 32 + ((rk ^ g) & 1) * 16;
        const uint32_t ta = sb + O_RAW + (n0 + (r8 & 4)) * BS + (mi ^ 1) * 64 + (r8 & 1) * 32 + (r8 & 2) * 8;
        const uint2* sp = prm.S->stats + (b & 3) * 2048 + tok;
        uint4 x[8];
        uint2 u[8];
        uint32_t G[32];
        float h[32];
        auto load = [&](int hf) {
            mbar_wait(sb + B_X + hf * 8);
#pragma unroll
            for (int i = 4 * hf; i < 4 * hf + 4; i++) x[i] = lds128(sb + xo + hw * 1024 + (i & 3) * 8192 + hf * (O_XB - O_XT));
        };
        auto poll = [&](int hf) {
            mbar_wait(sb + B_GO + hf * 8);
            TS(hw == 3 ? 16 + hf : 63);
            const uint2* v = u + 4 * hf;
            int it = 0;
#pragma unroll 1
            do {
#pragma unroll
                for (int i = 4 * hf; i < 4 * hf + 4; i++) u[i] = ldr64(sp + i * 256);
            } while (__any_sync(~0u, (int)(((v[0].x ^ tag) | (v[1].x ^ tag)) | ((v[2].x ^ tag) | (v[3].x ^ tag))) < 0) && ++it < 100000);
            TV(hw == 7 ? 61 + hf : 63, it);
            TS(hw == 3 ? (hf ? 25 : 18) : 63);
        };
        auto norm = [&](int i) {
            const float r = fabsf(__uint_as_float(u[i].x));
            float* v = h + 8 * (i & 3);
#pragma unroll
            for (int k = 0; k < 4; k++) {
                const uint32_t e = bsub_lo(comp(x[i], k), u[i].y);
                v[2 * k] = bf_lo(e) * r; v[2 * k + 1] = bf_hi(e) * r;
            }
            stsm4t(ta + i * 2 * TS8, pk_h(v[2], v[3]), pk_h(v[0], v[1]), pk_h(v[6], v[7]), pk_h(v[4], v[5]));
            if ((i & 3) == 3) { __syncwarp(); mbar_arrive_e(sb + B_RAW + (i & 4) * 2); }
        };
        auto gate = [&](int i) {
            uint32_t* v = G + 4 * i;
            const float* e = h + 8 * (i & 3);
#pragma unroll
            for (int k = 0; k < 4; k++) v[k] = pk_bf(fmaf(e[2 * k], ftanh(e[2 * k]), e[2 * k]), fmaf(e[2 * k + 1], ftanh(e[2 * k + 1]), e[2 * k + 1]));
            pin4(v[0], v[1], v[2], v[3], Z);
        };
        load(0); poll(0); norm(0); norm(1); norm(2); norm(3);
        TS(32 + hw);
        sched_fence(Z);
        gate(0); gate(1); gate(2); gate(3);
        TS(hw == 0 ? 20 : 63);
        load(1);
        pin4(x[7].x, x[7].y, x[7].z, x[7].w, Z);
        mbar_arrive_e(sb + B_XR);
        poll(1);
        mbar_wait(sb + B_XR);
        norm(4); norm(5); gate(4);
        sched_fence(Z);
        norm(6); gate(5);
        sched_fence(Z);
        gate(6);
        sched_fence(Z);
        norm(7);
        TS(hw == 3 ? 19 : 63);
        gate(7);
        TS(hw == 0 ? 21 : 63);
        if (RH2 < RH) asm volatile("setmaxnreg.dec.sync.aligned.u32 %0;" ::"n"(RH2));
        mbar_wait(sb + B_SEL);
        mbar_wait(sb + B_SEL + 8);
        if (hw == 0) {
            mbar_arrive_peer_e(pb + B_XF);
            if (lane == 0) prm.S->epoch[b] = lds32(sb + O_SEL + 32);
        }
        const uint32_t r0 = lds32(sb + O_SEL) - tok, r1 = lds32(sb + O_SEL + 16) - tok;
        const uint32_t mine = ((r0 & 255) ? 0 : 128 << (r0 >> 8)) | ((r1 & 255) ? 0 : 128 << (r1 >> 8));
        const uint32_t skip = __reduce_or_sync(~0u, mine);
        const bool loc = (hw >> 2) == rk;
        const int ln = lane_id();
        const uint32_t oa = (loc ? sb : pb) + O_XT + ln * 32 + ((rk * 4 ^ ln) & 4) * 4 + (hw & 3) * 1024, ob = B_O + (hw & 3) * 40;
        if (!loc) mbar_wait(sb + B_XF);
#pragma unroll
        for (int p = 0; p < 5; p++) {
            const int i0 = p < 4 ? 2 * p : 7, i1 = p < 3 ? 2 * p + 2 : p + 4;
            if (loc) mbar_expect_e(sb + ob + p * 8, (i1 - i0) * 512);
            if (p == 2 && b < NFFN) mbar_wait(sb + B_HR);
            mbar_wait(sb + B_Y + p * 8);
            TS(hw == 1 ? 26 + p : 63);
#pragma unroll
            for (int i = i0; i < i1; i++) {
                const uint4 s = ldsm4t(ta + (2 * i - 1) * TS8);
                x[i] = make_uint4(bfma(s.y, G[4 * i], x[i].x), bfma(s.x, G[4 * i + 1], x[i].y), bfma(s.w, G[4 * i + 2], x[i].z), bfma(s.z, G[4 * i + 3], x[i].w));
            }
            if (loc) {
#pragma unroll
                for (int i = i0; i < i1; i++) sts128(oa + i * 4096, x[i].x, x[i].y, x[i].z, x[i].w);
                mbar_wait(sb + ob + p * 8);
                TS(p == 4 ? 120 : 63);
                fence_async();
                __syncwarp();
#pragma unroll
                for (int i = i0; i < i1; i++)
                    tma5d_st_e(sb + O_XT + (hw & 3) * 1024 + i * 4096, &mo, q * 16, 4 * i + 2 * rk + ((skip >> i) & 128), hw & 3);
            } else {
#pragma unroll
                for (int i = i0; i < i1; i++) st_async(oa + i * 4096, x[i], pb + ob + p * 8);
            }
        }
        if (skip) {
#pragma unroll
            for (int i = 0; i < 8; i++)
                if ((skip & ~mine) >> (7 + i) & 1) prm.out[(tok + i * 256) * 128 + b] = x[i];
        }
        asm volatile("cp.async.bulk.commit_group; cp.async.bulk.wait_group.read 0;" ::: "memory");
        TS(40 + hw);
        TDUMP;
    } else {
        asm volatile("setmaxnreg.dec.sync.aligned.u32 %0;" ::"n"(480 - 2 * RM - 2 * RH));
        LANES;
        const int fw = w - 16;
        const CUtensorMap* m1 = &mg + rk;
        if (fw == 0) {
            asm volatile("{.reg .pred p; elect.sync _|p,0xffffffff; @p mbarrier.init.shared.b64 [%0],1; @p mbarrier.init.shared.b64 [%0+8],1; fence.mbarrier_init.release.cluster;\n"
                         "@p mbarrier.arrive.expect_tx.shared.b64 _,[%0],16384; @p mbarrier.arrive.expect_tx.shared.b64 _,[%0+8],16384;}" ::"r"(sb + B_ROW) : "memory");
            bar_arrive(5, 128);
            spin(t0 + ROW0);
            bulk_e(sb + O_ROWS, prm.u + b * 1024, sb + B_ROW, 16384);
            TS(6); TV(0, t0 & 0xfffff);
            spin(t0 + ROW1);
            bulk_e(sb + O_ROWS + 16384, prm.u + (128 + b) * 1024, sb + B_ROW + 8, 16384);
            bar_sync(7, 64);
            if (b < NFFN) {
#pragma unroll 1
                for (int i = 0; i < 12; i++) {
                    spin(t0 + W0 + ((b * WD) >> 7) + min(i, NPE) * WD);
                    if (i == 4) mbar_wait(sb + B_P1);
                    if (i == 10) mbar_wait(sb + B_XR);
                    tma3d_e(sb + (i < 8 ? O_RING + i * 8192 : O_RNG3 + ((i + 2) & 3) * 8192), m1, i * 64, q, sb + B_FULL + i * 8);
                }
            }
        } else {
            if (lane == 0) {
#pragma unroll
                for (int i = 0; i < 21; i++)
                    asm volatile("mbarrier.init.shared.b64 [%0],%1;" ::"r"(sb + B_FULL - 8 + 8 * fw + i * 24), "r"(i < 18 ? 1 : 8) : "memory");
            }
            __syncwarp();
            asm volatile("fence.mbarrier_init.release.cluster; barrier.cluster.arrive.relaxed.aligned;" ::: "memory");
            asm volatile("prefetch.tensormap [%0];" ::"l"(&md - 1 + fw));
            asm volatile("prefetch.tensormap [%0];" ::"l"(m1));
            bar_sync(5, 128);
            if (fw == 2)
#pragma unroll
                for (int i = 0; i < 8; i++) bar_arrive(i < 7 ? 9 + i : 6, 64);
            if (fw == 1) {
                bar_arrive(3, 288);
                bar_arrive(7, 64);
                mbar_expect_e(sb + B_H, 256);
                mbar_expect_e(sb + B_X, 32768);
                mbar_expect_e(sb + B_X + 8, 32768);
                asm volatile("barrier.cluster.wait.aligned;" ::: "memory");
#pragma unroll 1
                for (int i = 0; i < 8; i++) {
                    spin(t0 + (i < 4 ? GAT0 + i * GATD : GAT1 + (i & 3) * GATE));
                    tma5d_mc_e(sb + (i < 4 ? O_XT : O_XB) + (i & 3) * 8192 + rk * 4096, &mx, q * 16, i * 4 + rk * 2, sb + B_X + (i & 4) * 2);
                }
            }
        }
        if (fw == 2) {
            sts32(sb + O_ONE + lane * 4, 0x3f803f80u);
            __syncwarp();
            mbar_expect_e(sb + B_XS, 4096);
            spin(t0 + TGO0);
            mbar_arrive_e(sb + B_GO);
        }
        if (fw == 3) {
            uint32_t ep;
            asm volatile("ld.relaxed.gpu.global.u32 %0,[%1];" : "=r"(ep) : "l"(prm.S->epoch + b) : "memory");
            ep += 1;
            sts32(sb + O_SEL + 32, ep);
            float sw[4] = {0.f, 0.f, 0.f, 0.f};
#pragma unroll
            for (int k = 0; k < 4; k++) mma_bf(sw, ldg128(prm.wr + k * 32 + lane), 0x3f803f80u, 0x3f803f80u);
            float wsum = sw[0] + sw[2];
#pragma unroll
            for (int o = 4; o < 32; o <<= 1) wsum += __shfl_xor_sync(~0u, wsum, o);
            uint2* dst = prm.S->stats + c * 2048 + b * 8 + g;
            uint32_t pa = sb + O_PST + g * 48 + (lane & 1) * 16, ky = 0;
            const uint32_t id = (ep & 1) * 0x8000 + 2047 - (lane & 1) * 1024 - b * 8 - g;
#pragma unroll 1
            for (int hf = 0; hf < 2; hf++) {
                bar_sync(1 + 3 * hf, 288);
                float v[3];
#pragma unroll
                for (int k = 0; k < 3; k++) {
                    const uint4 t = lds128(pa + k * 384);
                    v[k] = (__uint_as_float(t.x) + __uint_as_float(t.y)) + (__uint_as_float(t.z) + __uint_as_float(t.w));
                    v[k] += __shfl_xor_sync(~0u, v[k], 1);
                }
                const float mean = v[2] * (1.f / 1024.f);
                const float var = fmaxf(fmaf(-mean, mean, v[0] * (1.f / 1024.f)), 0.f);
                const float rs = rcp(bfr(fsqrt(bfr(bfr(var) + 1e-5f))));
                const uint32_t mk = pk_bf(mean, fmaf(-bfr(mean), wsum, v[1]) * rs);
                str64(dst, __float_as_uint(0.5f * rs) | ep << 31, mk);
                if ((lane & 1) == hf) ky = ((mk ^ (((int)mk >> 31) | 0x80000000u)) & 0xffff0000u) | id;
                TS(hf ? 63 : 5);
                dst += 1024; pa += 1152;
            }
            const uint32_t k1 = __reduce_max_sync(~0u, ky), k2 = __reduce_max_sync(~0u, ky == k1 ? 0u : ky);
            str64(prm.S->keys + g * 128 + b, k1, k2);
            TS(48);
            mbar_arrive_e(sb + B_P1);
        }
        uint32_t wa[4];
#pragma unroll
        for (int i = 0; i < 4; i++) wa[i] = sb + O_RING + fw * 8192 + ((mi >> 1) * 8 + r8) * 128 + (((2 * i + (mi & 1)) ^ r8) << 4);
        uint32_t xs = sb + mi * 16 + ((r8 & 2) ? O_ONE : O_XSEL + fw * 128 + (r8 & 1) * 2064), xd = (r8 & 2) ? 0 : 512;
        uint32_t dst = ((rk * 32 + fw * 4 + c) * 112 + q) * 8 + g, hs = sb + O_HT + (r8 & 1) * 144 + mi * 16;
        pin4(wa[0], wa[1], wa[2], wa[3], Z); pin4(xs, xd, dst, hs, Z);
        mbar_wait(sb + B_P1);
        const uint32_t ep = lds32(sb + O_SEL + 32);
        if (fw >= 2) {
            const uint2* kp = prm.S->keys + ((b & 3) * 2 + (fw & 1)) * 128 + lane * 2;
            const uint32_t tag = ep << 15;
            mbar_wait(sb + B_RAW);
            spin(t0 + TTOP);
            uint4 k, l;
            int it = 0;
#pragma unroll 1
            do { k = ldr128(kp); l = ldr128(kp + 64); } while (__any_sync(~0u, (((k.x ^ tag) | (k.z ^ tag)) | ((l.x ^ tag) | (l.z ^ tag))) & 0x8000) && ++it < 100000);
            TV(fw == 2 ? 24 : 63, it);
            TS(fw == 2 ? 49 : 63);
            uint32_t ky = __reduce_max_sync(~0u, max(max(k.x, k.z), max(l.x, l.z)));
            if (fw & 1) ky = __reduce_max_sync(~0u, max(max(k.x == ky ? k.y : k.x, k.z == ky ? k.w : k.z), max(l.x == ky ? l.y : l.x, l.z == ky ? l.w : l.z)));
            const uint32_t tok = ~ky & 2047;
            if (b < NFFN) bulk_e(sb + O_XSEL + (fw & 1) * 2064, prm.u + tok * 128, sb + B_XS, 2048);
            sched_fence(Z);
            if (fw == 3) mbar_arrive_e(sb + B_GO + 8);
            uint2 rc;
#pragma unroll 1
            do rc = ldr64(prm.S->stats + (b & 3) * 2048 + tok); while (__any_sync(~0u, (int)(rc.x ^ tag << 16) < 0) && ++it < 100000);
            sts128(sb + O_SEL + (fw & 1) * 16, tok, pk_bf(0.f, sigm(bf_hi(ky ^ (~((int)ky >> 31) | 0x80000000u)))), rc.y << 16, __float_as_uint(2.f * fabsf(__uint_as_float(rc.x))));
            __syncwarp();
            mbar_arrive_e(sb + B_SEL + (fw & 1) * 8);
        }
        if (b < NFFN) {
            float h[4][4] = {};
            uint4 A[8], B[2];
            const bool c1 = c & 1, c2 = c & 2;
            const uint32_t s2 = O_RNG3 + ((fw ^ 2) - fw) * 8192, bf = sb + B_FULL + fw * 8;
#define SLOT(n) ((n) % 3 == 2 ? s2 : (n) % 3 * 32768)
            auto ldA = [&](int k, int n, int hf) { A[k] = ldsm4t(wa[k & 3] + SLOT(n) + hf * 4096 + (k >> 2) * 2048); };
            auto half = [&](const uint4& x, int n, int hf) {
                sched_fence(Z);
#pragma unroll
                for (int k = 0; k < 8; k++) {
                    mma_bf(h[k & 3], A[k], k < 4 ? x.x : x.z, k < 4 ? x.y : x.w);
                    if (n >= 0) ldA(k, n, hf);
                }
            };
            mbar_wait(bf);
#pragma unroll
            for (int k = 0; k < 8; k++) ldA(k, 0, 0);
            mbar_wait(sb + B_XS);
            TS(fw == 1 ? 50 : 63);
            B[0] = ldsm4(xs);
#pragma unroll
            for (int n = 0; n < 4; n++) {
                TS(64 + fw + 4 * n);
                B[1] = ldsm4(xs + 64);
                half(B[0], n, 1);
                xs += xd;
                if (n < 3) { mbar_wait(bf + 32 * n + 32); B[0] = ldsm4(xs); }
                half(B[1], n < 3 ? n + 1 : -1, 0);
                TS(96 + fw + 4 * n);
                if (n < 3) {
                    sched_fence(Z);
                    if (n >= PACE) spin(t0 + W0 + ((b * WD) >> 7) + (fw + 4 * n + 12 - LEAD) * WD);
                    tma3d_e(sb + O_RING + fw * 8192 + SLOT(n), n ? &md : m1, (n ? q : fw + 12) * 64, n ? rk * 8 + fw + 4 * n - 4 : q, bf + 32 * n + 96);
                }
            }
#pragma unroll
            for (int j = 0; j < 4; j += 2)
                sts128(sb + O_RING + fw * 8192 + j * 256 + lane * 16, __float_as_uint(c2 ? h[j + 1][0] : h[j][0]), __float_as_uint(c2 ? h[j + 1][1] : h[j][1]),
                       __float_as_uint(c2 ? h[j + 1][2] : h[j][2]), __float_as_uint(c2 ? h[j + 1][3] : h[j][3]));
            if (fw >= 2) {
                bar_arrive(2, 128);
            } else {
                const uint32_t pa = sb + O_RING + fw * 512 + (lane >> 1) * 32 + (lane & 1) * 8, ha = sb + O_HT + fw * 64 + c * 16 + g * 2;
                mbar_wait(sb + B_SEL);
                mbar_wait(sb + B_SEL + 8);
                mbar_wait(sb + B_XF);
                const uint2 n0 = lds64(sb + O_SEL + 8), n1 = lds64(sb + O_SEL + 24);
                bar_sync(2, 128);
                TS(fw == 0 ? 51 : 63);
                float t[3][4];
#pragma unroll
                for (int j = 0; j < 4; j++) {
                    const uint2 p = lds64(pa + j * 8192);
                    t[0][j] = __uint_as_float(p.x); t[1][j] = __uint_as_float(p.y); t[2][j] = __uint_as_float(lds32(pa + j * 8192 + 16));
                }
                const float cs = (t[2][0] + t[2][1]) + (t[2][2] + t[2][3]);
                uint32_t v = pk_bf(fmaf(-__uint_as_float(n0.x), cs, (t[0][0] + t[0][1]) + (t[0][2] + t[0][3])) * __uint_as_float(n0.y),
                                   fmaf(-__uint_as_float(n1.x), cs, (t[1][0] + t[1][1]) + (t[1][2] + t[1][3])) * __uint_as_float(n1.y));
                if (rk == 0) v = pk_bf(silu(bf_lo(v)), silu(bf_hi(v)));
                asm volatile("st.async.shared::cluster.mbarrier::complete_tx::bytes.b32 [%0],%1,[%2];" ::"r"(pb + O_HX + fw * 128 + lane * 4), "r"(v), "r"(pb + B_H) : "memory");
                mbar_wait(sb + B_H);
                v = bmul(v, lds32(sb + O_HX + fw * 128 + lane * 4));
                sts16(ha, v); sts16(ha + 144, v >> 16);
                __syncwarp();
                asm volatile("{.reg .pred p; elect.sync _|p,0xffffffff; @p mbarrier.arrive.shared.b64 _,[%0],4;}" ::"r"(sb + B_HR) : "memory");
            }
#pragma unroll
            for (int n = 4; n < 6; n++) {
                mbar_wait(bf + 32 * n);
                TS(64 + fw + 4 * n);
#pragma unroll
                for (int k = 0; k < 8; k++) ldA(k, n, 0);
                if (n == 4) {
                    mbar_wait(sb + B_HR);
                    TS(fw == 0 ? 52 : 63);
                    B[0] = ldsm4(hs); B[1] = ldsm4(hs + 64);
                }
#pragma unroll
                for (int k = 0; k < 16; k++) h[k >> 2][k & 3] = 0.f;
                half(B[0], n, 1);
                half(B[1], -1, 0);
#define PICK(k) __float_as_uint(c2 ? (c1 ? h[3][k] : h[2][k]) : (c1 ? h[1][k] : h[0][k]))
                uint2* yo = prm.S->yp + dst + (n - 4) * 16 * 112 * 8;
                str64(yo, (PICK(0) & ~1u) | (ep & 1), PICK(1)); str64(yo + 448, (PICK(2) & ~1u) | (ep & 1), PICK(3));
                TS(96 + fw + 4 * n);
            }
            TS(fw == 0 ? 63 : 52 + fw);
        }
        if (!NOFIX && fw == 0) {
            mbar_wait(sb + B_SEL);
            mbar_wait(sb + B_SEL + 8);
            const uint4 sel = lds128(sb + O_SEL + (lane & 8) * 2);
            const uint32_t ch = 2 * c + (g & 1), go = sel.x * 1024 + b * 8 + ch;
            uint32_t xv;
            uint32_t sa = sb + O_RAW - TS8 + (sel.x >> 4) * BS + ch * 32 + (sel.x & 15) * 2;
            uint32_t ba = __reduce_max_sync(~0u, sel.x >> 8);
            ba = sb + B_Y + (ba == 7 ? 4 : ba >> 1) * 8;
            asm volatile("ld.global.nc.u16 %0,[%1];" : "=r"(xv) : "l"((const uint16_t*)prm.u + go) : "memory");
            xv <<= 16;
            uint32_t j0 = 0, xn = __float_as_uint(bfr(bfr(__uint_as_float(xv) - __uint_as_float(sel.z)) * __uint_as_float(sel.w)));
            pin4(xv, xn, sa, j0, Z);
            const uint4* yp = (const uint4*)prm.S->yp + b * 224 + lane;
            spin(t0 + TFIX);
            uint4 v[7];
            int it = 0;
            uint32_t bad, sv;
#pragma unroll 1
            do {
#pragma unroll
                for (int j = 0; j < 7; j++) v[j] = ldr128(yp + j * 32);
                mbar_wait(ba);
                sv = lds16(sa);
                bad = 0;
#pragma unroll
                for (int j = 0; j < 7; j++) asm volatile("{.reg .b32 t; lop3.b32 t,%1,%2,%3,0x7e; or.b32 %0,%0,t;}" : "+r"(bad) : "r"(v[j].x), "r"(ep), "r"(v[j].z));
            } while (__any_sync(~0u, bad & 1) && ++it < 100000);
            TV(57, it);
            float y[4];
#pragma unroll
            for (int k = 0; k < 4; k++)
                y[k] = ((__uint_as_float(comp(v[0], k)) + __uint_as_float(comp(v[1], k))) + (__uint_as_float(comp(v[2], k)) + __uint_as_float(comp(v[3], k)))) +
                       ((__uint_as_float(comp(v[4], k)) + __uint_as_float(comp(v[5], k))) + __uint_as_float(comp(v[6], k)));
            const bool b2 = lane & 4, b3 = lane & 8;
            const float y0 = (b2 ? y[2] : y[0]) + __shfl_xor_sync(~0u, b2 ? y[0] : y[2], 4), y1 = (b2 ? y[3] : y[1]) + __shfl_xor_sync(~0u, b2 ? y[1] : y[3], 4);
            float t = (b3 ? y1 : y0) + __shfl_xor_sync(~0u, b3 ? y0 : y1, 8);
            t += __shfl_xor_sync(~0u, t, 16);
            const float gt = bfr(silu(bfr(__uint_as_float(xn) + bfr(bfr(t) * __uint_as_float(sel.y)))));
            TS(56);
            ((uint16_t*)prm.out)[go] = pk_bf(fmaf(bf_lo(sv), gt, __uint_as_float(xv)), 0.f);
            TS(7);
        }
        TDUMP;
    }
}

typedef CUresult (*EncFn)(CUtensorMap*, CUtensorMapDataType, cuuint32_t, void*, const cuuint64_t*, const cuuint64_t*,
                          const cuuint32_t*, const cuuint32_t*, CUtensorMapInterleave, CUtensorMapSwizzle,
                          CUtensorMapL2promotion, CUtensorMapFloatOOBfill);

void make_map(EncFn f, CUtensorMap* m, const void* p, int rank, const cuuint64_t* gd, const cuuint64_t* gs,
              const cuuint32_t* bd, CUtensorMapSwizzle sw) {
    const cuuint32_t es[5] = {1, 1, 1, 1, 1};
    f(m, CU_TENSOR_MAP_DATA_TYPE_BFLOAT16, rank, const_cast<void*>(p), gd, gs, bd, es, CU_TENSOR_MAP_INTERLEAVE_NONE, sw,
      CU_TENSOR_MAP_L2_PROMOTION_NONE, CU_TENSOR_MAP_FLOAT_OOB_FILL_NONE);
}

}

extern "C" void kernel_launch(void* const* d_in, const int* in_sizes, int n_in, void* d_out, int out_size) {
    (void)in_sizes; (void)n_in; (void)out_size;
    void* fp = nullptr;
    cudaDriverEntryPointQueryResult qr;
    cudaGetDriverEntryPoint("cuTensorMapEncodeTiled", &fp, cudaEnableDefault, &qr);
    EncFn enc = (EncFn)fp;
    Maps maps;
    CUtensorMap &mg = maps.m[0], &mu = maps.m[1], &md = maps.m[2], &mx = maps.m[3], &mo = maps.m[4];
    {
        const cuuint64_t gd[3] = {64, 1024, 56}, gs[2] = {7168, 128};
        const cuuint32_t bd[3] = {64, 64, 1};
        make_map(enc, &mg, d_in[9], 3, gd, gs, bd, CU_TENSOR_MAP_SWIZZLE_128B);
        make_map(enc, &mu, d_in[10], 3, gd, gs, bd, CU_TENSOR_MAP_SWIZZLE_128B);
    }
    {
        const cuuint64_t gd[3] = {64, 3584, 16}, gs[2] = {2048, 128};
        const cuuint32_t bd[3] = {64, 64, 1};
        make_map(enc, &md, d_in[11], 3, gd, gs, bd, CU_TENSOR_MAP_SWIZZLE_128B);
    }
    {
        const cuuint64_t gd[5] = {1024, 2, 32, 8, 4}, gs[4] = {16384, 131072, 2048, 32768};
        const cuuint32_t bd[5] = {16, 2, 2, 8, 4}, bo[5] = {16, 2, 2, 8, 1};
        make_map(enc, &mx, d_in[0], 5, gd, gs, bd, CU_TENSOR_MAP_SWIZZLE_32B);
        make_map(enc, &mo, d_out, 5, gd, gs, bo, CU_TENSOR_MAP_SWIZZLE_32B);
    }
    Params p;
    p.u = (const uint4*)d_in[0]; p.logA = (const uint2*)d_in[1]; p.Aim = (const uint2*)d_in[2];
    p.Cre = (const uint2*)d_in[3]; p.Cim = (const uint2*)d_in[4];
    p.logdt = (const uint16_t*)d_in[5]; p.Dsk = (const uint16_t*)d_in[6]; p.wr = (const uint4*)d_in[8];
    p.out = (uint4*)d_out;
    void* sp = nullptr;
    cudaGetSymbolAddress(&sp, g_scratch);
    p.S = (Scratch*)sp; p.zero = 0;
    cudaFuncSetAttribute(fused_kernel, cudaFuncAttributeMaxDynamicSharedMemorySize, SMEM_BYTES + 512);
    fused_kernel<<<128, 640, SMEM_BYTES + 512, cudaStreamPerThread>>>(p, maps);
}
```

```cpp
#include <cuda_runtime.h>
#include <cuda_bf16.h>
#include <cuda_fp16.h>
#include <cuda.h>
#include <stdint.h>

#define RM 120
#define RH 80
#define ORD 1
#define FSB 1
#define RH2 RH
#define RF2 (480 - 2 * RM - 2 * RH2)
#define KV 5
#define FM 1023
#define SBC 1
#define LATE 1
#define KLAGV 0
#define PSY 1
#define FO 0
#define NOFIX 0
#define NFFN 112
namespace {

constexpr int RING = 8;
constexpr uint32_t BS = 272, TS8 = 8 * BS;
constexpr uint32_t O_RING = 0;
constexpr uint32_t O_XT   = RING * 8192;
constexpr uint32_t O_RAW  = O_XT + 32768 + TS8;
constexpr uint32_t O_XB   = O_RAW + 8 * TS8 + 128;
constexpr uint32_t O_HX   = O_RAW + 16 * TS8;
constexpr uint32_t O_HT   = O_HX + 256;
constexpr uint32_t O_RNG3 = 133 * 1024;
constexpr uint32_t O_PST  = O_RNG3 + 3 * 8192;
constexpr uint32_t O_PRIV = O_RNG3 + 32768;
constexpr uint32_t PRIV   = 7744;
constexpr uint32_t P_TAB  = 4224;
constexpr uint32_t O_XSEL = O_XT + 6 * 4096;
constexpr uint32_t O_ROWS = (RING - 4) * 8192;
constexpr uint32_t O_SEL  = O_PRIV + 8 * PRIV;
constexpr uint32_t O_ONE  = O_SEL + 64;
constexpr uint32_t O_BAR  = O_ONE + 128;
constexpr uint32_t B_ROW = O_BAR, B_FULL = B_ROW + 16, B_H = B_FULL + 8 * 24, B_SEL = B_H + 8, B_P1 = B_SEL + 16,
                   B_X = B_P1 + 8, B_GO = B_X + 16, B_XS = B_GO + 16, B_XF = B_XS + 8, B_O = B_XF + 8, B_Y = B_O + 160, B_RAW = B_Y + 40, B_HR = B_RAW + 16, B_XR = B_HR + 8;
constexpr uint32_t SMEM_BYTES = B_Y + 72;
static_assert(B_Y - B_FULL == 18 * 24 && O_XB % 256 == 0 && O_HT + 288 <= O_RNG3 && O_XB + 32768 <= O_RNG3 + 16384, "layout");
static_assert(SMEM_BYTES + 512 <= 232448, "smem");
constexpr int PB = 1216, T2 = 2368, T3 = T2 + 640;

#define SCHED(X) X(0, ROW0, 330) X(1, ROW1, 1020) X(2, NPE, 11) X(3, GAT0, 900) X(4, GAT1, 2200) X(5, GATD, 60) X(6, TGO0, 2850) \
    X(7, TTOP, 4000) X(8, W0, 1750) X(9, WD, 280) X(10, LEAD, 1) X(11, GATE, 500) X(13, TFIX, 10020) X(14, PACE, 0) X(15, KLAG, KLAGV)
#define X(i, n, v) constexpr int n = v;

struct Scratch {
    uint2 stats[4 * 2048];
    uint2 keys[8 * 128];
    uint2 yp[128 * 56 * 8];
    unsigned epoch[128];
    int ts[128 * 128];
};
__device__ Scratch g_scratch;

struct Maps { CUtensorMap m[5]; };
struct Params {
    const uint4* u; const uint2* logA; const uint2* Aim; const uint2* Cre; const uint2* Cim;
    const uint16_t* logdt; const uint16_t* Dsk; const uint4* wr;
    uint4* out; Scratch* S; uint32_t zero;
};

#define DI __device__ __forceinline__
DI int lane_id() { int l; asm volatile("mov.u32 %0,%%laneid;" : "=r"(l)); __builtin_assume(l >= 0 && l < 32); return l; }
DI int now_ns() { int c; asm volatile("mov.u32 %0,%%globaltimer_lo;" : "=r"(c)::"memory"); return c; }
DI void spin(int t) {
    asm volatile("{.reg .pred p; .reg .s32 c; L: mov.u32 c,%%globaltimer_lo; sub.s32 c,c,%0; setp.lt.s32 p,c,0; @p nanosleep.u32 32; @p bra.uni L;}" ::"r"(t) : "memory");
}
DI void mbar_arrive_e(uint32_t b) { asm volatile("{.reg .pred p; elect.sync _|p,0xffffffff; @p mbarrier.arrive.shared.b64 _,[%0];}" ::"r"(b) : "memory"); }
DI void mbar_expect_e(uint32_t b, int tx) { asm volatile("{.reg .pred p; elect.sync _|p,0xffffffff; @p mbarrier.arrive.expect_tx.shared.b64 _,[%0],%1;}" ::"r"(b), "r"(tx) : "memory"); }
DI void mbar_wait(uint32_t b) {
    asm volatile("{.reg .pred p; W: mbarrier.try_wait.parity.shared.b64 p,[%0],0; @!p bra.uni W; }" ::"r"(b) : "memory");
}
DI void bulk_e(uint32_t dst, const void* src, uint32_t bar, int bytes) {
    asm volatile("{.reg .pred p; elect.sync _|p,0xffffffff; @p cp.async.bulk.shared::cluster.global.mbarrier::complete_tx::bytes [%0],[%1],%3,[%2];}" ::"r"(dst), "l"(src), "r"(bar), "r"(bytes) : "memory");
}
DI void tma3d_e(uint32_t dst, const CUtensorMap* m, int c1, int c2, uint32_t bar) {
    asm volatile("{.reg .pred p; elect.sync _|p,0xffffffff; @p mbarrier.arrive.expect_tx.shared.b64 _,[%2],8192;\n"
                 "@p cp.async.bulk.tensor.3d.shared::cluster.global.mbarrier::complete_tx::bytes [%0],[%1,{0,%3,%4}],[%2];}" ::"r"(dst), "l"(m), "r"(bar), "r"(c1), "r"(c2) : "memory");
}
DI void tma5d_mc_e(uint32_t dst, const CUtensorMap* m, int c0, int c2, uint32_t bar) {
    asm volatile("{.reg .pred p; elect.sync _|p,0xffffffff;\n"
                 "@p cp.async.bulk.tensor.5d.shared::cluster.global.mbarrier::complete_tx::bytes.multicast::cluster [%0],[%1,{%3,0,%4,0,0}],[%2],%5;}"
                 ::"r"(dst), "l"(m), "r"(bar), "r"(c0), "r"(c2), "h"((uint16_t)3) : "memory");
}
DI void tma5d_st_e(uint32_t src, const CUtensorMap* m, int c0, int c2, int c4) {
    asm volatile("{.reg .pred p; elect.sync _|p,0xffffffff; @p cp.async.bulk.tensor.5d.global.shared::cta.bulk_group [%1,{%2,0,%3,0,%4}],[%0];}" ::"r"(src), "l"(m), "r"(c0), "r"(c2), "r"(c4) : "memory");
}
DI void mbar_arrive_peer_e(uint32_t b) { asm volatile("{.reg .pred p; elect.sync _|p,0xffffffff; @p mbarrier.arrive.relaxed.cluster.shared::cluster.b64 _,[%0];}" ::"r"(b) : "memory"); }
DI void st_async(uint32_t dst, const uint4& v, uint32_t bar) {
    asm volatile("st.async.shared::cluster.mbarrier::complete_tx::bytes.v4.b32 [%0],{%1,%2,%3,%4},[%5];" ::"r"(dst), "r"(v.x), "r"(v.y), "r"(v.z), "r"(v.w), "r"(bar) : "memory");
}
DI void fence_async() { asm volatile("fence.proxy.async.shared::cta;" ::: "memory"); }
DI void bar_sync(int id, int n) { asm volatile("bar.sync %0,%1;" ::"r"(id), "r"(n) : "memory"); }
DI void bar_arrive(int id, int n) { asm volatile("bar.arrive %0,%1;" ::"r"(id), "r"(n) : "memory"); }
DI uint4 ldg128(const void* p) { uint4 v; asm volatile("ld.global.nc.v4.u32 {%0,%1,%2,%3},[%4];" : "=r"(v.x), "=r"(v.y), "=r"(v.z), "=r"(v.w) : "l"(p) : "memory"); return v; }
DI uint2 ldg64(const void* p) { uint2 v; asm volatile("ld.global.nc.v2.u32 {%0,%1},[%2];" : "=r"(v.x), "=r"(v.y) : "l"(p) : "memory"); return v; }
DI uint4 ldr128(const void* p) {
    uint4 v;
    asm volatile("{.reg .b128 t; .reg .b64 a,b; ld.relaxed.gpu.global.b128 t,[%4]; mov.b128 {a,b},t; mov.b64 {%0,%1},a; mov.b64 {%2,%3},b;}"
                 : "=r"(v.x), "=r"(v.y), "=r"(v.z), "=r"(v.w) : "l"(p) : "memory");
    return v;
}
DI uint2 ldr64(const void* p) { uint2 v; asm volatile("{.reg .b64 t; ld.relaxed.gpu.global.b64 t,[%2]; mov.b64 {%0,%1},t;}" : "=r"(v.x), "=r"(v.y) : "l"(p) : "memory"); return v; }
DI void str64(void* p, uint32_t x, uint32_t y) { asm volatile("{.reg .b64 t; mov.b64 t,{%1,%2}; st.relaxed.gpu.global.b64 [%0],t;}" ::"l"(p), "r"(x), "r"(y) : "memory"); }
DI uint32_t lds32(uint32_t a) { uint32_t v; asm volatile("ld.shared.u32 %0,[%1];" : "=r"(v) : "r"(a) : "memory"); return v; }
DI uint32_t lds16(uint32_t a) { uint32_t v; asm volatile("ld.shared.u16 %0,[%1];" : "=r"(v) : "r"(a) : "memory"); return v; }
DI uint2 lds64(uint32_t a) { uint2 v; asm volatile("ld.shared.v2.u32 {%0,%1},[%2];" : "=r"(v.x), "=r"(v.y) : "r"(a) : "memory"); return v; }
DI uint4 lds128(uint32_t a) { uint4 v; asm volatile("ld.shared.v4.u32 {%0,%1,%2,%3},[%4];" : "=r"(v.x), "=r"(v.y), "=r"(v.z), "=r"(v.w) : "r"(a) : "memory"); return v; }
DI void sts16(uint32_t a, uint32_t v) { asm volatile("st.shared.u16 [%0],%1;" ::"r"(a), "r"(v) : "memory"); }
DI void sts32(uint32_t a, uint32_t v) { asm volatile("st.shared.u32 [%0],%1;" ::"r"(a), "r"(v) : "memory"); }
DI void sts64(uint32_t a, uint32_t x, uint32_t y) { asm volatile("st.shared.v2.u32 [%0],{%1,%2};" ::"r"(a), "r"(x), "r"(y) : "memory"); }
DI void sts128(uint32_t a, uint32_t x, uint32_t y, uint32_t z, uint32_t w) { asm volatile("st.shared.v4.u32 [%0],{%1,%2,%3,%4};" ::"r"(a), "r"(x), "r"(y), "r"(z), "r"(w) : "memory"); }
DI uint4 ldsm4(uint32_t a) { uint4 v; asm volatile("ldmatrix.sync.aligned.m8n8.x4.shared.b16 {%0,%1,%2,%3},[%4];" : "=r"(v.x), "=r"(v.y), "=r"(v.z), "=r"(v.w) : "r"(a) : "memory"); return v; }
DI uint4 ldsm4t(uint32_t a) { uint4 v; asm volatile("ldmatrix.sync.aligned.m8n8.x4.trans.shared.b16 {%0,%1,%2,%3},[%4];" : "=r"(v.x), "=r"(v.y), "=r"(v.z), "=r"(v.w) : "r"(a) : "memory"); return v; }
DI void stsm4(uint32_t a, uint32_t x, uint32_t y, uint32_t z, uint32_t w) { asm volatile("stmatrix.sync.aligned.m8n8.x4.shared.b16 [%0],{%1,%2,%3,%4};" ::"r"(a), "r"(x), "r"(y), "r"(z), "r"(w) : "memory"); }
DI void stsm4t(uint32_t a, uint32_t x, uint32_t y, uint32_t z, uint32_t w) { asm volatile("stmatrix.sync.aligned.m8n8.x4.trans.shared.b16 [%0],{%1,%2,%3,%4};" ::"r"(a), "r"(x), "r"(y), "r"(z), "r"(w) : "memory"); }
DI void mma_bf(float (&d)[4], uint32_t a0, uint32_t a1, uint32_t a2, uint32_t a3, uint32_t b0, uint32_t b1) {
    asm("mma.sync.aligned.m16n8k16.row.col.f32.bf16.bf16.f32 {%0,%1,%2,%3},{%4,%5,%6,%7},{%8,%9},{%0,%1,%2,%3};"
        : "+f"(d[0]), "+f"(d[1]), "+f"(d[2]), "+f"(d[3]) : "r"(a0), "r"(a1), "r"(a2), "r"(a3), "r"(b0), "r"(b1));
}
DI void mma_bf(float (&d)[4], const uint4& a, uint32_t b0, uint32_t b1) { mma_bf(d, a.x, a.y, a.z, a.w, b0, b1); }
typedef uint32_t h4[2];
DI void mma_h(h4& d, const uint4& a, uint32_t b0, uint32_t b1) {
    asm("mma.sync.aligned.m16n8k16.row.col.f16.f16.f16.f16 {%0,%1},{%2,%3,%4,%5},{%6,%7},{%0,%1};"
        : "+r"(d[0]), "+r"(d[1]) : "r"(a.x), "r"(a.y), "r"(a.z), "r"(a.w), "r"(b0), "r"(b1));
}
DI void mma_k8(h4& d, uint32_t a0, uint32_t a1, uint32_t b0) {
    asm("mma.sync.aligned.m16n8k8.row.col.f16.f16.f16.f16 {%0,%1},{%2,%3},{%4},{%0,%1};" : "+r"(d[0]), "+r"(d[1]) : "r"(a0), "r"(a1), "r"(b0));
}
DI void mma_cvt(float (&d)[4], const h4& a, uint32_t b) {
    asm("mma.sync.aligned.m16n8k8.row.col.f32.f16.f16.f32 {%0,%1,%2,%3},{%4,%5},{%6},{%7,%7,%7,%7};"
        : "=f"(d[0]), "=f"(d[1]), "=f"(d[2]), "=f"(d[3]) : "r"(a[0]), "r"(a[1]), "r"(b), "f"(0.f));
}
DI uint32_t pk_bf(float lo, float hi) { uint32_t r; asm("cvt.rn.bf16x2.f32 %0,%1,%2;" : "=r"(r) : "f"(hi), "f"(lo)); return r; }
DI uint32_t pk_h(float lo, float hi) { uint32_t r; asm("cvt.rn.f16x2.f32 %0,%1,%2;" : "=r"(r) : "f"(hi), "f"(lo)); return r; }
DI float bf_lo(uint32_t v) { return __uint_as_float(v << 16); }
DI float bf_hi(uint32_t v) { return __uint_as_float(v & 0xffff0000u); }
DI float bfr(float x) { return bf_lo(pk_bf(x, 0.f)); }
DI uint32_t hadd(uint32_t a, uint32_t b) { uint32_t r; asm("add.rn.f16x2 %0,%1,%2;" : "=r"(r) : "r"(a), "r"(b)); return r; }
DI uint32_t hsub(uint32_t a, uint32_t b) { uint32_t r; asm volatile("sub.rn.f16x2 %0,%1,%2;" : "=r"(r) : "r"(a), "r"(b)); return r; }
DI uint32_t hscl(uint32_t a) { uint32_t r; asm("mul.rn.f16x2 %0,%1,%2;" : "=r"(r) : "r"(a), "r"(0x01000100)); return r; }
DI uint32_t bsub_lo(uint32_t x, uint32_t m) { uint32_t r; asm("{.reg .b16 l,h; .reg .b32 t; mov.b32 {l,h},%2; mov.b32 t,{l,l}; sub.rn.bf16x2 %0,%1,t;}" : "=r"(r) : "r"(x), "r"(m)); return r; }
DI uint32_t bmul(uint32_t a, uint32_t b) { uint32_t r; asm("mul.rn.bf16x2 %0,%1,%2;" : "=r"(r) : "r"(a), "r"(b)); return r; }
DI uint32_t bfma(uint32_t a, uint32_t b, uint32_t c) { uint32_t r; asm("fma.rn.bf16x2 %0,%1,%2,%3;" : "=r"(r) : "r"(a), "r"(b), "r"(c)); return r; }
DI float ex2(float x) { float r; asm("ex2.approx.ftz.f32 %0,%1;" : "=f"(r) : "f"(x)); return r; }
DI float rcp(float x) { float r; asm("rcp.approx.ftz.f32 %0,%1;" : "=f"(r) : "f"(x)); return r; }
DI float ftanh(float x) { float r; asm("tanh.approx.f32 %0,%1;" : "=f"(r) : "f"(x)); return r; }
DI float fsqrt(float x) { float r; asm("sqrt.approx.ftz.f32 %0,%1;" : "=f"(r) : "f"(x)); return r; }
constexpr float LOG2E = 1.4426950408889634f;
DI float sigm(float x) { return rcp(1.f + ex2(-LOG2E * x)); }
DI float silu(float x) { return x * sigm(x); }
struct cf { float r, i; };
DI cf cmul(cf a, cf b) { return {fmaf(a.r, b.r, -a.i * b.i), fmaf(a.r, b.i, a.i * b.r)}; }
DI float mul2(float a, float b) { float r; asm("{.reg .f32 t; mul.f32 t,%1,%2; mul.f32 %0,t,0f40000000;}" : "=f"(r) : "f"(a), "f"(b)); return r; }
DI cf csq(cf a) { return {fmaf(a.r, a.r, -a.i * a.i), mul2(a.r, a.i)}; }
DI cf csqc(cf a) { return {fmaf(a.r, a.r, -a.i * a.i), mul2(a.r, -a.i)}; }
DI cf cexp(float a2, float be, float p) { float m = ex2(a2 * p); float t = be * p; return {m * __cosf(t), m * __sinf(t)}; }

struct ch2 { uint32_t r, i; };
template <int V>
DI ch2 hmul(ch2 a, uint32_t fr, uint32_t fi) {
    ch2 o;
    if (V) asm("{.reg .b32 t,u; mul.rn.f16x2 t,%3,%5; neg.f16x2 t,t; mul.rn.f16x2 u,%2,%5; fma.rn.f16x2 %0,%2,%4,t; fma.rn.f16x2 %1,%3,%4,u;}"
               : "=&r"(o.r), "=r"(o.i) : "r"(a.r), "r"(a.i), "r"(fr), "r"(fi));
    else asm("{.reg .b32 t,u,n; mul.rn.f16x2 t,%2,%4; mul.rn.f16x2 u,%3,%4; neg.f16x2 n,%3; fma.rn.f16x2 %0,n,%5,t; fma.rn.f16x2 %1,%2,%5,u;}"
             : "=&r"(o.r), "=r"(o.i) : "r"(a.r), "r"(a.i), "r"(fr), "r"(fi));
    return o;
}
DI ch2 hmul(ch2 a, uint32_t f) {
    ch2 o;
    asm("{.reg .b32 t,u,x,y; .reg .b16 l,h; mov.b32 {l,h},%4; mov.b32 x,{l,l}; mov.b32 y,{h,h};\n"
        "mul.rn.f16x2 t,%3,y; neg.f16x2 t,t; fma.rn.f16x2 %0,%2,x,t; mul.rn.f16x2 u,%3,x; fma.rn.f16x2 %1,%2,y,u;}"
        : "=&r"(o.r), "=r"(o.i) : "r"(a.r), "r"(a.i), "r"(f));
    return o;
}
DI uint32_t pk_h(cf f) { return pk_h(f.r, f.i); }
DI void sts_ch2(uint32_t a, ch2 x, ch2 y, ch2 z, ch2 w) { sts128(a, x.r, y.r, z.r, w.r); sts128(a + 512, x.i, y.i, z.i, w.i); }

#define TDUMP
#define TS(i)
#define TV(i, v)
#define T2S(i)

DI void sched_fence(uint32_t Z) { if (FSB == 2) { asm volatile("griddepcontrol.launch_dependents;" ::: "memory"); return; } asm volatile("{.reg .pred p; setp.ne.u32 p,%0,0; @p griddepcontrol.launch_dependents;}" ::"r"(Z) : "memory"); }
DI uint32_t copy(uint32_t v, uint32_t Z) { uint32_t r; asm volatile("xor.b32 %0,%1,%2;" : "=r"(r) : "r"(v), "r"(Z)); return r; }
DI void pin4(uint32_t& a, uint32_t& b, uint32_t& c, uint32_t& d, uint32_t Z) {
    asm volatile("{.reg .pred p; setp.ne.u32 p,%4,0; @p ld.shared.v4.u32 {%0,%1,%2,%3},[%4];}" : "+r"(a), "+r"(b), "+r"(c), "+r"(d) : "r"(Z) : "memory");
}

#define BFRAG(B, s) ((s) & 1) ? B[(s) >> 1].z : B[(s) >> 1].x, ((s) & 1) ? B[(s) >> 1].w : B[(s) >> 1].y
DI uint32_t comp(const uint4& v, int k) { return k == 0 ? v.x : k == 1 ? v.y : k == 2 ? v.z : v.w; }
template <bool FIRST>
DI void conv_half(h4 (&acc)[16], uint32_t aA, uint32_t aB, uint32_t bar, uint32_t Z) {
    constexpr int O = FIRST ? 0 : 8, NT = FIRST ? 5 : 4;
    uint4 A[4], S[2], B[4] = {}, A32, A64, Y;
    h4 P[4], m1[5] = {};
    auto refill = [&](int k, int j) {
        const uint32_t a = aA + j * 32 + k * 512;
        A[2 * k].y = j < 7 ? copy(A[2 * k].z, Z) : lds32(a + 16); A[2 * k].x = lds32(a); A[2 * k].z = lds32(a - 16);
        A[2 * k + 1].w = j < 7 ? copy(A[2 * k + 1].x, Z) : lds32(a + 272); A[2 * k + 1].y = lds32(a + 256); A[2 * k + 1].x = lds32(a + 240);
    };
    auto diff = [&](int k, int j) {
        uint4 &a = A[2 * k], &c = A[2 * k + 1];
        a.w = copy(a.x, Z); c.z = copy(c.y, Z);
        S[k].y = j < 7 ? copy(S[k].z, Z) : hsub(a.y, c.w); S[k].z = hsub(a.z, c.x); S[k].x = hsub(a.x, c.y); S[k].w = hsub(a.w, c.z);
    };
    auto pre = [&](int s) { P[s][0] = hsub(B[s].w, B[s].x); P[s][1] = hsub(B[s].z, B[s].y); };
    auto extra = [&](int j, int t, uint32_t b0, uint32_t b1) {
        if (j == 1 && O + t + 4 < 16) mma_k8(acc[O + t + 4], Y.x, Y.y, b1);
        if (j == 1 && FIRST) mma_k8(acc[t + 8], Y.z, Y.w, b1);
        if (j == 0 && O + t + 4 < 16) mma_h(acc[O + t + 4], A32, b0, b1);
        if (j == 0 && FIRST) mma_h(acc[t + 8], A64, b0, b1);
    };
    refill(0, 7); refill(1, 7);
    if (!FIRST)
#pragma unroll
        for (int k = 0; k < 2 * NT; k++) acc[O + (k | 1)][k & 1] = hsub(acc[O + (k | 1)][k & 1], acc[O + (k & ~1)][k & 1]);
    diff(0, 7);
    if (FIRST) { pin4(A[0].x, A[0].y, A[0].z, A[0].w, Z); pin4(A[1].x, A[1].y, A[1].z, A[1].w, Z); pin4(S[0].x, S[0].y, S[0].z, S[0].w, Z); }
    mbar_wait(bar);
#pragma unroll
    for (int i = 0; i < 4; i++) B[i] = ldsm4(aB - 7 * BS + i * 2 * TS8);
#pragma unroll
    for (int j = 7; j >= 0; j--) {
        if (j == 2) { Y.x = lds32(aA + 1040); Y.y = Y.x & Z; if (FIRST) { Y.z = lds32(aA + 1104); Y.w = Y.z & Z; } }
#pragma unroll
        for (int s = 0; s < 4; s++) {
            if (s) pre(s - 1);
            if (s == 2) diff(1, j);
            mma_h(acc[O + 2 * s], A[0], B[s].x, B[s].y); mma_h(m1[s], A[1], B[s].z, B[s].w);
            if (FM >> s & 1) sched_fence(Z);
        }
        pre(3);
        if (j) refill(0, j - 1);
        if (j == 0) {
            A32.x = lds32(aA + 1024); A32.y = copy(Y.x, Z); A32.z = lds32(aA + 1008); A32.w = copy(A32.x, Z);
            if (FIRST) { A64.x = lds32(aA + 1088); A64.y = copy(Y.z, Z); A64.z = copy(Y.w, Z); A64.w = copy(A64.x, Z); }
        }
#pragma unroll
        for (int s = 0; s < 4; s++) {
            if (s + 1 < NT) { mma_h(acc[O + 2 * s + 2], A[2], B[s].x, B[s].y); mma_h(m1[s + 1], A[3], B[s].z, B[s].w); }
            if (j) extra(j, 2 * s, B[s].x, B[s].y);
            if (j) { if (s + 1 < NT && (FM >> (4 + s + !FIRST) & 1)) sched_fence(Z); B[s] = ldsm4(aB - (j - 1) * BS + s * 2 * TS8); }
        }
        if (j) refill(1, j - 1);
#pragma unroll
        for (int s = 0; s < 4; s++) mma_h(acc[O + 2 * ((s + !FIRST) & 3) + 1], S[0], P[(s + !FIRST) & 3][0], P[(s + !FIRST) & 3][1]);
        if (j) { if (FM >> 8 & 1) sched_fence(Z); diff(0, j - 1); }
        if (FIRST) mma_h(acc[9], S[1], P[3][0], P[3][1]);
#pragma unroll
        for (int s = 0; s < 3; s++) mma_h(acc[O + 2 * s + 3], S[1], P[s][0], P[s][1]);
#pragma unroll
        for (int s = 3; s >= 0; s--) { if (!j) extra(j, 2 * s, B[s].x, B[s].y); extra(j, 2 * s + 1, P[s][0], P[s][1]); }
        if (j && (FM >> 9 & 1)) sched_fence(Z);
    }
#pragma unroll
    for (int k = 0; k < 16 - O; k++) {
        const uint32_t e = acc[O + (k & ~1)][k & 1];
        acc[O + (k | 1)][k & 1] = hadd(k < 2 * NT ? hadd(e, m1[k >> 1][k & 1]) : e, acc[O + (k | 1)][k & 1]);
    }
#pragma unroll
    for (int k = 0; k < (FIRST ? 10 : 6); k++) acc[O + 2 + (k & ~1)][k & 1] = hadd(acc[O + 2 + (k & ~1)][k & 1], m1[k >> 1][k & 1]);
}

__global__ void __cluster_dims__(2, 1, 1) __launch_bounds__(640, 1)
fused_kernel(const __grid_constant__ Params prm, const __grid_constant__ Maps maps) {
    const CUtensorMap &mg = maps.m[0], &md = maps.m[2], &mx = maps.m[3], &mo = maps.m[4];
    extern __shared__ __align__(1024) unsigned char smem_raw[];
    SCHED(X)
    const uint32_t tid = threadIdx.x;
    uint2 vA, vI, vR, vC;
    uint32_t ldt, Dsk;
    if (tid < 256) {
        const int e = blockIdx.x * 256 + tid;
        asm volatile("ld.global.nc.u16 %0,[%1];" : "=r"(ldt) : "l"(prm.logdt + (e >> 5)) : "memory");
        asm volatile("ld.global.nc.u16 %0,[%1];" : "=r"(Dsk) : "l"(prm.Dsk + (e >> 5)) : "memory");
        vA = ldg64(prm.logA + e); vI = ldg64(prm.Aim + e); vR = ldg64(prm.Cre + e); vC = ldg64(prm.Cim + e);
    }
    const int t0 = __shfl_sync(~0u, now_ns() + (threadIdx.x >> 10), 0);
    uint32_t sb = (uint32_t)__cvta_generic_to_shared(smem_raw);
    if (SBC) sb = __shfl_sync(~0u, sb + (threadIdx.x >> 10), 0);
    const int b = blockIdx.x, rk = b & 1, q = b >> 1;
    const int w = __shfl_sync(~0u, tid >> 5, 0);
#define LANES const int lane = lane_id(), g = lane >> 2, c = lane & 3, mi = lane >> 3, r8 = lane & 7; (void)g; (void)c; (void)mi; (void)r8
    uint32_t pb;
    asm("mapa.shared::cluster.u32 %0,%1,%2;" : "=r"(pb) : "r"(sb), "r"(rk ^ 1));
    if (w < 17) asm volatile("barrier.cluster.arrive.relaxed.aligned;" ::: "memory");
    const uint32_t Z = prm.zero;

    if (w < 8) {
        LANES;
        const uint32_t pv = sb + O_PRIV + w * PRIV, tb = pv + P_TAB, rw = sb + O_RAW + w * 32;
        const uint32_t dd = g - 2 * c;
        uint32_t st = pv + lane * 16, cyP = pv + 528 + c * 1056 + mi * 4, Zr = Z;
        uint32_t a1 = tb + ((dd + 14) & 4) * (PB / 4) + ((dd + 14) >> 3) * 16 + ((dd + 14) & 3) * 4, t2 = tb + T2 + dd * 8;
        uint32_t aB = rw + r8 * BS + (mi >> 1) * TS8 + ((mi ^ mi >> 1) & 1) * 16, ac0 = rw + lane * BS;
        uint32_t fa = pv + 16 + r8 * 16 + mi * 528, fb = fa + ((mi & 1) ? -528 : 512), fc = (mi < 2 ? fa : fb) + 4 * 528;
        uint32_t Id = (dd >> 1) ? 0 : 0x400 << (16 * (g & 1)), kt = pv + (mi * 8 + (r8 >> 1) + (r8 & 1) * 4) * 16;
        uint32_t w2 = tb + T2 + (lane & 1) * 320 + (lane >> 1) * 8, w3 = tb + T3 + lane * 4;
        sts64(rw - TS8 + g * BS + c * 8, 0, 0);
        sts128(tb + (mi & 1) * PB + (r8 < 2 ? r8 : r8 + 64) * 16, 0, 0, 0, 0);
        h4 kd[6] = {};
        uint32_t lA = pv + (mi >> 1) * 512 + (mi & 1) * 128 + r8 * 16, lB = pv + (2 + mi) * 512 + r8 * 16;
        uint32_t lC = pv + (6 + (mi & 1)) * 512 + (mi >> 1) * 128 + r8 * 16, lF = pv + 4096 + (mi & 1) * 64 + (mi >> 1) * 16;
        uint32_t sF = pv + 4096 + lane * 2, j0 = 0;
        pin4(a1, t2, aB, ac0, Z); pin4(fa, fb, fc, cyP, Z); pin4(st, Zr, Id, kt, Z); pin4(lA, lB, lC, lF, Z); pin4(sF, w2, w3, j0, Z);
        sched_fence(Z);
        if (!LATE) asm volatile("setmaxnreg.inc.sync.aligned.u32 %0;" ::"n"(RM));
        const float dt = bfr(ex2(bf_lo(ldt + (lane & Z)) * LOG2E));
        uint32_t mx2 = __vmaxu2(__vmaxu2(vR.x & 0x7fff7fffu, vR.y & 0x7fff7fffu), __vmaxu2(vC.x & 0x7fff7fffu, vC.y & 0x7fff7fffu));
        const int ex = min(max(max((int)((__reduce_max_sync(~0u, max(mx2 >> 16, mx2 & 0xffffu)) >> 7) + (__float_as_uint(dt) >> 23)), (int)((Dsk >> 7) & 255) + 109), 228), 369);
        const float cs = dt * __uint_as_float((387 - ex) << 23), dl = -dt * LOG2E, ncs = __uint_as_float(__float_as_uint(cs) ^ 0x80000000u ^ Z);
        TS(88 + w); T2S(0);
        auto gen = [&](uint32_t sel) {
            const float a2 = bfr(ex2(__uint_as_float(__byte_perm(vA.x, vA.y, sel) & 0xffff0000u) * LOG2E)) * dl;
            const float be = __uint_as_float(__byte_perm(vI.x, vI.y, sel) & 0xffff0000u) * dt;
            const cf wv = {__uint_as_float(__byte_perm(vR.x, vR.y, sel) & 0xffff0000u) * cs, __uint_as_float(__byte_perm(vC.x, vC.y, sel) & 0xffff0000u) * ncs};
            const cf y1 = cexp(a2, -be, 1.f), y2 = csq(y1), y4 = csq(y2), z8 = csqc(y4), z16 = csq(z8), z32 = csq(z16);
            const cf z64 = cexp(a2, be, 64.f);
            {
                const uint32_t f = pk_h(z64) ^ Z, f16 = pk_h(z16);
                const ch2 m0 = {pk_h(1.f, z32.r), pk_h(0.f, z32.i)}, m1 = hmul(m0, pk_h(z8));
                sts_ch2(st, m0, m1, hmul(m0, f16), hmul(m1, f16));
                sts16(sF, f); sts16(sF + 64, f >> 16);
            }
            if (KV & 4) sched_fence(Z);
            {
                const cf w4 = cmul(wv, y4), y256 = csqc(csq(z64)), y512 = csq(y256);
                const uint32_t f2 = pk_h(y2), f256 = pk_h(y256), f512 = pk_h(y512);
                const ch2 p0 = {pk_h(wv.r, w4.r), pk_h(wv.i, w4.i)};
                const ch2 p1 = hmul(p0, pk_h(y1)), p2 = hmul(p0, f2), p4 = hmul(p0, pk_h(y4));
                sts_ch2(st + 1024, p1, p2, hmul(p1, f2), p4);
                if (KV & 8) sched_fence(Z);
                const ch2 e1 = hmul(p4, f256);
                const ch2 e2 = hmul(p4, f512), e3 = hmul(e1, f512);
                sts_ch2(st + 2048, hmul(p2, f256), e1, e2, e3);
                const ch2 g0 = {__byte_perm(e2.r, e3.r, 0x7632), __byte_perm(e2.i, e3.i, 0x7632)}, s0 = hmul(g0, f512);
                sts_ch2(st + 3072, s0, hmul(s0, f512), p0, g0);
            }
            __syncwarp();
        };
        auto mul = [&]() {
#pragma unroll
            for (int k2 = 0; k2 < 2; k2++) {
                const uint4 M = ldsm4t(lA + k2 * 256), F = ldsm4(lF + k2 * 32);
                uint4 B[3];
                B[0] = ldsm4t(lB + k2 * 256); B[1] = ldsm4t(lB + k2 * 256 + 128); B[2] = ldsm4t(lC + k2 * 256);
#pragma unroll
                for (int i = 1; i >= 0; i--) {
                    const uint32_t fr = i ? F.z : F.x, fi = i ? F.w : F.y;
                    const ch2 m0 = {i ? M.y ^ Z : (KV & 1) ? M.x ^ Z : M.x, i ? M.w ^ Z : (KV & 1) ? M.z ^ Z : M.z}, m1 = hmul<1>(m0, fr, fi), m2 = hmul<0>(m1, fr, fi), m3 = hmul<1>(m2, fr, fi);
                    const uint4 A0 = make_uint4(m0.r, m1.r, m0.i, m1.i), A1 = make_uint4(m2.r, m3.r, m2.i, m3.i);
                    if (KV & 2) sched_fence(Z);
                    mma_h(kd[0], A0, B[i].x, B[i].y); mma_h(kd[1], A0, B[i].z, B[i].w); mma_h(kd[2], A0, i ? B[2].z : B[2].x, i ? B[2].w : B[2].y);
                    mma_h(kd[3], A1, B[i].x, B[i].y); mma_h(kd[4], A1, B[i].z, B[i].w); mma_h(kd[5], A1, i ? B[2].z : B[2].x, i ? B[2].w : B[2].y);
                }
            }
            __syncwarp();
        };
        if (w >= 4 && KLAG) spin(t0 + KLAG);
        gen(0x1044);
        if (LATE) asm volatile("setmaxnreg.inc.sync.aligned.u32 %0;" ::"n"(RM));
        bar_sync(w < 7 ? 9 + w : 6, 64);
#pragma unroll 1
        for (uint32_t sel = 0x3244; sel < 0x8000; sel += 0x2200) {
            mul();
            gen(sel);
        }
        mul();
        TS(w == 0 ? 59 : w == 4 ? 60 : 63); T2S(1);
        {
#pragma unroll
            for (int nt = 0; nt < 3; nt++) stsm4(kt + nt * 512, kd[nt][0], kd[nt][1], kd[nt + 3][0], kd[nt + 3][1]);
            __syncwarp();
            uint4 R0 = lds128(st), R1 = lds128(st + 512), R2 = lds128(st + 1024);
            R0.x = hscl(R0.x); R0.y = hscl(R0.y); R0.z = hscl(R0.z); R0.w = hscl(R0.w);
            R1.x = hscl(R1.x); R1.y = hscl(R1.y); R1.z = hscl(R1.z); R1.w = hscl(R1.w);
            R2.x = hscl(R2.x); R2.y = hscl(R2.y); R2.z = hadd(hscl(R2.z), pk_h(bf_lo(Dsk) * __uint_as_float((370 - ex) << 23), 0.f));
            const bool l31 = lane == 31, l2 = lane < 2;
            uint32_t nx = __shfl_down_sync(~0u, R0.x, 1);
            if (l31) nx = R0.w >> 16;
            const uint32_t pr = __shfl_sync(~0u, l31 ? R0.w : R1.y, lane - 1);
            const uint32_t sA = __shfl_sync(~0u, R1.z, lane - 2), sB = __shfl_sync(~0u, R1.w, lane - 2);
            const uint32_t s0 = __shfl_sync(~0u, R2.x, lane - 2), s1 = __shfl_sync(~0u, R2.y, lane - 2);
            sts128(st + P_TAB + 32, __byte_perm(R0.y, R0.x, 0x5410), __byte_perm(R0.z, R0.y, 0x5410), __byte_perm(R0.w, R0.z, 0x5410), __byte_perm(R0.x, R0.w, 0x5432));
            sts128(st + P_TAB + PB + 32, __byte_perm(R0.y, R0.x, 0x7632), __byte_perm(R0.z, R0.y, 0x7632), __byte_perm(R0.w, R0.z, 0x7632), __byte_perm(R0.w, nx, 0x3254));
            const uint32_t d1 = __byte_perm(R1.y, 0, 0x1010), d3 = __byte_perm(R1.y, 0, 0x3232);
            sts128(st + P_TAB + 544, __byte_perm(pr, R1.x, 0x3254), __byte_perm(R1.y, R1.x, 0x5410), d1, d1);
            sts128(st + P_TAB + PB + 544, __byte_perm(R1.x, R1.y, 0x5432), __byte_perm(R1.y, R1.x, 0x7632), d3, d3);
            uint32_t a = w2;
            const uint32_t pA = l2 ? 0 : sA, pB = l2 ? sA : sB, pT = l2 ? sB : 0;
            sts64(a, __byte_perm(R1.z, pA, 0x5410), __byte_perm(R1.z, pA, 0x7632));
            sts64(a + 128, __byte_perm(R1.w, pB, 0x5410), __byte_perm(R1.w, pB, 0x7632));
            if (lane < 16) sts64(a + 256, pT << 16, pT & 0xffff0000u);
            a = w3;
            const uint32_t p0 = __byte_perm(0, s0, l2 ? 0x5432 : 0x7654), p1 = __byte_perm(s0, s1, l2 ? 0x5432 : 0x7654);
            sts32(a, __byte_perm(R2.x, p0, 0x5410)); sts32(a + 128, __byte_perm(R2.x, p0, 0x7632));
            sts32(a + 256, __byte_perm(R2.y, p1, 0x5410)); sts32(a + 384, __byte_perm(R2.y, p1, 0x7632));
            if (lane == 0) sts64(st + P_TAB + PB + 24, R2.z & 0xffffu, __byte_perm(R0.x, R2.z, 0x5410));
            if (l31) {
                sts64(st + P_TAB + 35 * 16, d3, d3 << 16);
                sts128(st + P_TAB + 39 * 16, 0, R1.w >> 16, __byte_perm(R1.w, 0, 0x3232), R1.w & 0xffff0000u);
            }
        }
        __syncwarp();
        TS(1); T2S(9);
        h4 acc[16] = {};
        const uint32_t t3 = t2 + T3 - T2, fo = st + 16;
        Id *= min(ex, 257) - 227;
        sts16(sb + O_SEL + 48 + w * 2, (max(ex, 257) - 130) << 7);
        auto put_tiles = [&](int i0, int i1, int bar) {
#pragma unroll
            for (int i = i0; i < i1; i++) {
                float d[4], e[4];
                mma_cvt(d, acc[2 * i], Id);
                mma_cvt(e, acc[2 * i + 1], Id);
                stsm4t(aB + (2 * i - 1) * TS8, pk_bf(d[0], d[1]), pk_bf(d[2], d[3]), pk_bf(e[2], e[3]), pk_bf(e[0], e[1]));
            }
            __syncwarp();
            mbar_arrive_e(sb + B_Y + bar * 8);
        };
        uint32_t U[13], cy;
        auto fetch = [&](int p) {
            const uint32_t ac = ac0 + p * 4 * TS8;
            const uint4 q2 = lds128(ac), q3 = lds128(ac + 16);
            cy = p ? lds32(cyP + 512) : 0;
            const uint2 q0 = lds64(ac - BS + 8);
            const uint4 q1 = lds128(ac - BS + 16);
            U[0] = q0.x; U[1] = q0.y; U[2] = q1.x; U[3] = q1.y; U[4] = q1.z; U[5] = q1.w; U[6] = q2.x; U[7] = q2.y; U[8] = q2.z; U[9] = q2.w;
            U[10] = q3.x; U[11] = q3.y; U[12] = q3.z;
            __syncwarp();
        };
        auto filter = [&](int p) {
            if (p < 2 || c < 2) sts32(cyP, cy);
            uint32_t Q[13], Pp[12], P4[12], C3[12], C5[10];
#pragma unroll
            for (int k = 1; k < 13; k++) Q[k] = __byte_perm(U[k - 1], U[k], 0x5432);
#pragma unroll
            for (int k = 1; k < 12; k++) Pp[k] = hadd(U[k], Q[k]);
#pragma unroll
            for (int k = 2; k < 12; k++) P4[k] = hadd(Pp[k], Pp[k - 1]);
#pragma unroll
            for (int k = 3; k < 12; k++) C3[k] = hadd(Pp[k], Q[k + 1]);
#pragma unroll
            for (int k = 1; k < 10; k++) C5[k] = hadd(P4[k + 1], U[k - 1]);
            if (FO & 1) {
                sts128(fo, C3[4], C3[5], C3[6], C3[7]); sts128(fo + 528, C3[8], C3[9], C3[10], C3[11]);
                sts128(fo + 2 * 528, C5[2], C5[3], C5[4], C5[5]); sts128(fo + 3 * 528, C5[6], C5[7], C5[8], C5[9]);
            }
            if (FO & 2) sched_fence(Zr);
            if (p < 2)
#pragma unroll
                for (int h = 0; h < 2; h++) {
                    const int k = 2 + 4 * h;
                    sts128(fo + (4 + h) * 528, hadd(P4[k], C3[k + 1]), hadd(P4[k + 1], C3[k + 2]), hadd(P4[k + 2], C3[k + 3]), hadd(P4[k + 3], C3[k + 4]));
                    sts128(fo + (6 + h) * 528, hadd(P4[k + 2], C5[k - 1]), hadd(P4[k + 3], C5[k]), hadd(P4[k + 4], C5[k + 1]), hadd(P4[k + 5], C5[k + 2]));
                }
            if (FO & 4) sched_fence(Zr);
            if (!(FO & 1)) {
                sts128(fo, C3[4], C3[5], C3[6], C3[7]); sts128(fo + 528, C3[8], C3[9], C3[10], C3[11]);
                sts128(fo + 2 * 528, C5[2], C5[3], C5[4], C5[5]); sts128(fo + 3 * 528, C5[6], C5[7], C5[8], C5[9]);
            }
            __syncwarp();
        };
        uint2 T[5], U2[5], V[8];
        uint4 Fa[4], Fb[4], Fc[4];
        auto taps = [&](int nv) {
#pragma unroll
            for (int D = 0; D < 5; D++) { T[D] = lds64(t2 + D * 64); U2[D] = lds64(t2 + 320 + D * 64); }
#pragma unroll
            for (int D = 0; D < nv; D++) V[D] = lds64(t3 + D * 64);
        };
        auto coarse = [&](int p, int t0, int t1, int lv) {
#pragma unroll
            for (int gl = 0; gl < 4; gl++) {
#pragma unroll
                for (int t = t0; t < t1; t++) { const int D = t - 4 * p - gl - 4; if ((lv & 1) && D >= 0 && D < 5) mma_h(acc[t], Fa[gl], T[D].x, T[D].y); }
#pragma unroll
                for (int t = t0; t < t1; t++) { const int D = t - 4 * p - gl - 4; if ((lv & 2) && D >= 0 && D < 5) mma_h(acc[t], Fb[gl], U2[D].x, U2[D].y); }
#pragma unroll
                for (int t = t1 - 1; t >= t0; t--) { const int D = t - 4 * p - gl - 8; if ((lv & 4) && D >= 0) mma_h(acc[t], Fc[gl], V[D].x, V[D].y); }
            }
        };
        auto frags = [&](int lv) {
#pragma unroll
            for (int gl = 0; gl < 4; gl++) {
                if (lv & 1) Fa[gl] = ldsm4t(fa + gl * 128);
                if (lv & 2) Fb[gl] = ldsm4t(fb + gl * 128);
                if (lv & 4) Fc[gl] = ldsm4t(fc + gl * 128);
            }
        };
        T2S(10);
        conv_half<true>(acc, a1, aB, sb + B_RAW, Zr);
        T2S(11);
        fetch(0);
        put_tiles(0, 2, 0);
        filter(0);
        taps(8);
        frags(1); coarse(0, 4, 16, 1);
        frags(6); coarse(0, 4, 16, 6);
        fetch(1);
        put_tiles(2, 4, 1);
        filter(1);
        if (!ORD) { frags(1); coarse(1, 8, 16, 1); frags(6); coarse(1, 8, 16, 6); }
        T2S(22);
        conv_half<false>(acc, a1, aB + 8 * TS8, sb + B_RAW + 8, Zr);
        T2S(23);
        if (PSY & 2) bar_sync(9 + (w & 3), 64);
        if (ORD) {
            taps(0);
            frags(3);
            fetch(2);
            coarse(1, 8, PSY & 1 ? 12 : 16, 3);
            put_tiles(4, 6, 2);
            if (PSY & 1) { bar_sync(9 + (w & 3), 64); coarse(1, 12, 16, 3); }
            filter(2);
#pragma unroll
            for (int D = 0; D < 4; D++) V[D] = lds64(t3 + D * 64);
            frags(7);
            coarse(1, 12, 16, 4);
            coarse(2, 12, ORD == 1 ? 14 : 16, 3);
            put_tiles(6, 7, 3);
            if (ORD == 1) {
                if (PSY & 4) bar_sync(9 + (w & 3), 64); else sched_fence(Zr);
                h4 e[2] = {};
#pragma unroll
                for (int gl = 0; gl < 4; gl++)
#pragma unroll
                    for (int t = 1; t >= 0; t--)
                        if (t + 2 - gl >= 0) { mma_h(acc[14 + t], Fa[gl], T[t + 2 - gl].x, T[t + 2 - gl].y); mma_h(e[t], Fb[gl], U2[t + 2 - gl].x, U2[t + 2 - gl].y); }
#pragma unroll
                for (int k = 0; k < 4; k++) acc[14 + (k >> 1)][k & 1] = hadd(acc[14 + (k >> 1)][k & 1], e[k >> 1][k & 1]);
            }
        } else {
            fetch(2);
            put_tiles(4, 6, 2);
            filter(2);
            taps(0);
            frags(3); coarse(2, 12, 16, 3);
            put_tiles(6, 7, 3);
        }
        put_tiles(7, 8, 4);
        T2S(24);
        TS(3);
        TDUMP;
    } else if (w < 16) {
        LANES;
        const int hw = w - 8;
        if (RH < 96) asm volatile("setmaxnreg.dec.sync.aligned.u32 %0;" ::"n"(RH));
        if (RH > 96) asm volatile("setmaxnreg.inc.sync.aligned.u32 %0;" ::"n"(RH));
        uint32_t tag;
        asm volatile("ld.relaxed.gpu.global.u32 %0,[%1];" : "=r"(tag) : "l"(prm.S->epoch + b) : "memory");
        tag = ~tag << 31;
        {
            uint32_t W[16];
#pragma unroll
            for (int k = 0; k < 4; k++) {
                const uint4 v = ldg128(prm.wr + hw * 16 + (k ^ (g & 1)) * 4 + c);
                W[4 * k] = v.x; W[4 * k + 1] = v.y; W[4 * k + 2] = v.z; W[4 * k + 3] = v.w;
            }
#pragma unroll
            for (int k = 0; k < 16; k++) if (g & 2) W[k] = 0x3f803f80u;
            const bool dg = mi == c, od = g & 1;
            uint32_t ra = sb + O_ROWS + g * 2048 + hw * 256 + od * 64 + c * 16;
            uint32_t pa = sb + O_PST + ((dg ? 0 : 8 + 4 * (g & 2)) + 2 * c + od) * 48 + hw * 4;
            TS(hw == 4 ? 22 : 63);
            bar_sync(3, 288);
#pragma unroll 1
            for (int hf = 0; hf < 2; hf++) {
                float d[4] = {}, e[4] = {};
                mbar_wait(sb + B_ROW + hf * 8);
                TS(hw == 4 ? (hf ? 23 : 58) : 63);
#pragma unroll
                for (int k = 0; k < 4; k++) {
                    const uint4 x = lds128((ra ^ ((k & 1) << 6)) + (k >> 1) * 128);
                    mma_bf(d, x.x ^ Z, W[4 * k], x.y ^ Z, W[4 * k + 1], x.x, x.y);
                    mma_bf(e, x.z ^ Z, W[4 * k + 2], x.w ^ Z, W[4 * k + 3], x.z, x.w);
                }
#define PICK2(e) (dg ? (od ? e[1] : e[0]) : (od ? e[3] : e[2]))
                sts32(pa, __float_as_uint(PICK2(d) + PICK2(e)));
                TS(hf ? 63 : 8 + hw);
                bar_arrive(1 + 3 * hf, 288);
                ra += 16384; pa += 1152;
            }
        }
        const int n0 = hw + (hw & 4);
        const uint32_t tok = n0 * 16 + (lane & 2) * 32 + (lane & 1) * 8 + g, xo = O_XT + lane * 32 + ((rk ^ g) & 1) * 16;
        const uint32_t ta = sb + O_RAW + (n0 + (r8 & 4)) * BS + (mi ^ 1) * 64 + (r8 & 1) * 32 + (r8 & 2) * 8;
        const uint2* sp = prm.S->stats + (b & 3) * 2048 + tok;
        uint4 x[8];
        uint2 u[8];
        uint32_t G[32];
        float h[32];
        auto load = [&](int hf) {
            mbar_wait(sb + B_X + hf * 8);
#pragma unroll
            for (int i = 4 * hf; i < 4 * hf + 4; i++) x[i] = lds128(sb + xo + hw * 1024 + (i & 3) * 8192 + hf * (O_XB - O_XT));
        };
        auto poll = [&](int hf) {
            mbar_wait(sb + B_GO + hf * 8);
            TS(hw == 3 ? 16 + hf : 63);
            const uint2* v = u + 4 * hf;
            int it = 0;
#pragma unroll 1
            do {
#pragma unroll
                for (int i = 4 * hf; i < 4 * hf + 4; i++) u[i] = ldr64(sp + i * 256);
            } while (__any_sync(~0u, (int)(((v[0].x ^ tag) | (v[1].x ^ tag)) | ((v[2].x ^ tag) | (v[3].x ^ tag))) < 0) && ++it < 100000);
            TV(hw == 7 ? 61 + hf : 63, it);
            TS(hw == 3 ? (hf ? 25 : 18) : 63);
        };
        auto norm = [&](int i) {
            const float r = fabsf(__uint_as_float(u[i].x));
            float* v = h + 8 * (i & 3);
#pragma unroll
            for (int k = 0; k < 4; k++) {
                const uint32_t e = bsub_lo(comp(x[i], k), u[i].y);
                v[2 * k] = bf_lo(e) * r; v[2 * k + 1] = bf_hi(e) * r;
            }
            stsm4t(ta + i * 2 * TS8, pk_h(v[2], v[3]), pk_h(v[0], v[1]), pk_h(v[6], v[7]), pk_h(v[4], v[5]));
            if ((i & 3) == 3) { __syncwarp(); mbar_arrive_e(sb + B_RAW + (i & 4) * 2); }
        };
        auto gate = [&](int i) {
            uint32_t* v = G + 4 * i;
            const float* e = h + 8 * (i & 3);
#pragma unroll
            for (int k = 0; k < 4; k++) v[k] = pk_bf(fmaf(e[2 * k], ftanh(e[2 * k]), e[2 * k]), fmaf(e[2 * k + 1], ftanh(e[2 * k + 1]), e[2 * k + 1]));
            pin4(v[0], v[1], v[2], v[3], Z);
        };
        load(0); poll(0); norm(0); norm(1); norm(2); norm(3);
        TS(32 + hw);
        sched_fence(Z);
        gate(0); gate(1); gate(2); gate(3);
        TS(hw == 0 ? 20 : 63);
        load(1);
        pin4(x[7].x, x[7].y, x[7].z, x[7].w, Z);
        mbar_arrive_e(sb + B_XR);
        poll(1);
        mbar_wait(sb + B_XR);
        norm(4); norm(5); gate(4);
        sched_fence(Z);
        norm(6); gate(5);
        sched_fence(Z);
        gate(6);
        sched_fence(Z);
        norm(7);
        TS(hw == 3 ? 19 : 63);
        gate(7);
        TS(hw == 0 ? 21 : 63);
        if (RH2 < RH) asm volatile("setmaxnreg.dec.sync.aligned.u32 %0;" ::"n"(RH2));
        mbar_wait(sb + B_SEL);
        mbar_wait(sb + B_SEL + 8);
        if (hw == 0) {
            mbar_arrive_peer_e(pb + B_XF);
            if (lane == 0) prm.S->epoch[b] = lds32(sb + O_SEL + 32);
        }
        const uint32_t r0 = lds32(sb + O_SEL) - tok, r1 = lds32(sb + O_SEL + 16) - tok;
        const uint32_t mine = ((r0 & 255) ? 0 : 128 << (r0 >> 8)) | ((r1 & 255) ? 0 : 128 << (r1 >> 8));
        const uint32_t skip = __reduce_or_sync(~0u, mine);
        const bool loc = (hw >> 2) == rk;
        const int ln = lane_id();
        const uint32_t oa = (loc ? sb : pb) + O_XT + ln * 32 + ((rk * 4 ^ ln) & 4) * 4 + (hw & 3) * 1024, ob = B_O + (hw & 3) * 40;
        if (!loc) mbar_wait(sb + B_XF);
#pragma unroll
        for (int p = 0; p < 5; p++) {
            const int i0 = p < 4 ? 2 * p : 7, i1 = p < 3 ? 2 * p + 2 : p + 4;
            if (loc) mbar_expect_e(sb + ob + p * 8, (i1 - i0) * 512);
            if (p == 2 && b < NFFN) mbar_wait(sb + B_HR);
            mbar_wait(sb + B_Y + p * 8);
            TS(hw == 1 ? 26 + p : 63);
            if (p == 0) {
                const uint4 r = lds128(sb + O_SEL + 48);
                if (__any_sync(~0u, ((r.x | r.y | r.z | r.w) & 0x40004000u) != 0))
#pragma unroll
                    for (int k = 0; k < 32; k++) G[k] = bmul(G[k], comp(r, k & 3));
            }
#pragma unroll
            for (int i = i0; i < i1; i++) {
                const uint4 s = ldsm4t(ta + (2 * i - 1) * TS8);
                x[i] = make_uint4(bfma(s.y, G[4 * i], x[i].x), bfma(s.x, G[4 * i + 1], x[i].y), bfma(s.w, G[4 * i + 2], x[i].z), bfma(s.z, G[4 * i + 3], x[i].w));
            }
            if (loc) {
#pragma unroll
                for (int i = i0; i < i1; i++) sts128(oa + i * 4096, x[i].x, x[i].y, x[i].z, x[i].w);
                mbar_wait(sb + ob + p * 8);
                TS(p == 4 ? 120 : 63);
                fence_async();
                __syncwarp();
#pragma unroll
                for (int i = i0; i < i1; i++)
                    tma5d_st_e(sb + O_XT + (hw & 3) * 1024 + i * 4096, &mo, q * 16, 4 * i + 2 * rk + ((skip >> i) & 128), hw & 3);
            } else {
#pragma unroll
                for (int i = i0; i < i1; i++) st_async(oa + i * 4096, x[i], pb + ob + p * 8);
            }
        }
        if (skip) {
#pragma unroll
            for (int i = 0; i < 8; i++)
                if ((skip & ~mine) >> (7 + i) & 1) prm.out[(tok + i * 256) * 128 + b] = x[i];
        }
        asm volatile("cp.async.bulk.commit_group; cp.async.bulk.wait_group.read 0;" ::: "memory");
        TS(40 + hw);
        TDUMP;
    } else {
        asm volatile("setmaxnreg.dec.sync.aligned.u32 %0;" ::"n"(480 - 2 * RM - 2 * RH));
        LANES;
        const int fw = w - 16;
        const CUtensorMap* m1 = &mg + rk;
        if (fw == 0) {
            asm volatile("{.reg .pred p; elect.sync _|p,0xffffffff; @p mbarrier.init.shared.b64 [%0],1; @p mbarrier.init.shared.b64 [%0+8],1; fence.mbarrier_init.release.cluster;\n"
                         "@p mbarrier.arrive.expect_tx.shared.b64 _,[%0],16384; @p mbarrier.arrive.expect_tx.shared.b64 _,[%0+8],16384;}" ::"r"(sb + B_ROW) : "memory");
            bar_arrive(5, 128);
            spin(t0 + ROW0);
            bulk_e(sb + O_ROWS, prm.u + b * 1024, sb + B_ROW, 16384);
            TS(6); TV(0, t0 & 0xfffff);
            spin(t0 + ROW1);
            bulk_e(sb + O_ROWS + 16384, prm.u + (128 + b) * 1024, sb + B_ROW + 8, 16384);
            bar_sync(7, 64);
            if (b < NFFN) {
#pragma unroll 1
                for (int i = 0; i < 12; i++) {
                    spin(t0 + W0 + ((b * WD) >> 7) + min(i, NPE) * WD);
                    if (i == 4) mbar_wait(sb + B_P1);
                    if (i == 10) mbar_wait(sb + B_XR);
                    tma3d_e(sb + (i < 8 ? O_RING + i * 8192 : O_RNG3 + ((i + 2) & 3) * 8192), m1, i * 64, q, sb + B_FULL + i * 8);
                }
            }
        } else {
            if (lane == 0) {
#pragma unroll
                for (int i = 0; i < 21; i++)
                    asm volatile("mbarrier.init.shared.b64 [%0],%1;" ::"r"(sb + B_FULL - 8 + 8 * fw + i * 24), "r"(i < 18 ? 1 : 8) : "memory");
            }
            __syncwarp();
            asm volatile("fence.mbarrier_init.release.cluster; barrier.cluster.arrive.relaxed.aligned;" ::: "memory");
            asm volatile("prefetch.tensormap [%0];" ::"l"(&md - 1 + fw));
            asm volatile("prefetch.tensormap [%0];" ::"l"(m1));
            bar_sync(5, 128);
            if (fw == 2)
#pragma unroll
                for (int i = 0; i < 8; i++) bar_arrive(i < 7 ? 9 + i : 6, 64);
            if (fw == 1) {
                bar_arrive(3, 288);
                bar_arrive(7, 64);
                mbar_expect_e(sb + B_H, 256);
                mbar_expect_e(sb + B_X, 32768);
                mbar_expect_e(sb + B_X + 8, 32768);
                asm volatile("barrier.cluster.wait.aligned;" ::: "memory");
#pragma unroll 1
                for (int i = 0; i < 8; i++) {
                    spin(t0 + (i < 4 ? GAT0 + i * GATD : GAT1 + (i & 3) * GATE));
                    tma5d_mc_e(sb + (i < 4 ? O_XT : O_XB) + (i & 3) * 8192 + rk * 4096, &mx, q * 16, i * 4 + rk * 2, sb + B_X + (i & 4) * 2);
                }
            }
        }
        if (fw == 2) {
            sts32(sb + O_ONE + lane * 4, 0x3f803f80u);
            __syncwarp();
            mbar_expect_e(sb + B_XS, 4096);
            spin(t0 + TGO0);
            mbar_arrive_e(sb + B_GO);
        }
        if (fw == 3) {
            uint32_t ep;
            asm volatile("ld.relaxed.gpu.global.u32 %0,[%1];" : "=r"(ep) : "l"(prm.S->epoch + b) : "memory");
            ep += 1;
            sts32(sb + O_SEL + 32, ep);
            float sw[4] = {0.f, 0.f, 0.f, 0.f};
#pragma unroll
            for (int k = 0; k < 4; k++) mma_bf(sw, ldg128(prm.wr + k * 32 + lane), 0x3f803f80u, 0x3f803f80u);
            float wsum = sw[0] + sw[2];
#pragma unroll
            for (int o = 4; o < 32; o <<= 1) wsum += __shfl_xor_sync(~0u, wsum, o);
            uint2* dst = prm.S->stats + c * 2048 + b * 8 + g;
            uint32_t pa = sb + O_PST + g * 48 + (lane & 1) * 16, ky = 0;
            const uint32_t id = (ep & 1) * 0x8000 + 2047 - (lane & 1) * 1024 - b * 8 - g;
#pragma unroll 1
            for (int hf = 0; hf < 2; hf++) {
                bar_sync(1 + 3 * hf, 288);
                float v[3];
#pragma unroll
                for (int k = 0; k < 3; k++) {
                    const uint4 t = lds128(pa + k * 384);
                    v[k] = (__uint_as_float(t.x) + __uint_as_float(t.y)) + (__uint_as_float(t.z) + __uint_as_float(t.w));
                    v[k] += __shfl_xor_sync(~0u, v[k], 1);
                }
                const float mean = v[2] * (1.f / 1024.f);
                const float var = fmaxf(fmaf(-mean, mean, v[0] * (1.f / 1024.f)), 0.f);
                const float rs = rcp(bfr(fsqrt(bfr(bfr(var) + 1e-5f))));
                const uint32_t mk = pk_bf(mean, fmaf(-bfr(mean), wsum, v[1]) * rs);
                str64(dst, __float_as_uint(0.5f * rs) | ep << 31, mk);
                if ((lane & 1) == hf) ky = ((mk ^ (((int)mk >> 31) | 0x80000000u)) & 0xffff0000u) | id;
                TS(hf ? 63 : 5);
                dst += 1024; pa += 1152;
            }
            const uint32_t k1 = __reduce_max_sync(~0u, ky), k2 = __reduce_max_sync(~0u, ky == k1 ? 0u : ky);
            str64(prm.S->keys + g * 128 + b, k1, k2);
            TS(48);
            mbar_arrive_e(sb + B_P1);
        }
        uint32_t wa[4];
#pragma unroll
        for (int i = 0; i < 4; i++) wa[i] = sb + O_RING + fw * 8192 + ((mi >> 1) * 8 + r8) * 128 + (((2 * i + (mi & 1)) ^ r8) << 4);
        uint32_t xs = sb + mi * 16 + ((r8 & 2) ? O_ONE : O_XSEL + fw * 128 + (r8 & 1) * 2064), xd = (r8 & 2) ? 0 : 512;
        uint32_t dst = ((rk * 32 + fw * 4 + c) * 112 + q) * 8 + g, hs = sb + O_HT + (r8 & 1) * 144 + mi * 16;
        pin4(wa[0], wa[1], wa[2], wa[3], Z); pin4(xs, xd, dst, hs, Z);
        mbar_wait(sb + B_P1);
        const uint32_t ep = lds32(sb + O_SEL + 32);
        if (fw >= 2) {
            const uint2* kp = prm.S->keys + ((b & 3) * 2 + (fw & 1)) * 128 + lane * 2;
            const uint32_t tag = ep << 15;
            mbar_wait(sb + B_RAW);
            spin(t0 + TTOP);
            uint4 k, l;
            int it = 0;
#pragma unroll 1
            do { k = ldr128(kp); l = ldr128(kp + 64); } while (__any_sync(~0u, (((k.x ^ tag) | (k.z ^ tag)) | ((l.x ^ tag) | (l.z ^ tag))) & 0x8000) && ++it < 100000);
            TV(fw == 2 ? 24 : 63, it);
            TS(fw == 2 ? 49 : 63);
            uint32_t ky = __reduce_max_sync(~0u, max(max(k.x, k.z), max(l.x, l.z)));
            if (fw & 1) ky = __reduce_max_sync(~0u, max(max(k.x == ky ? k.y : k.x, k.z == ky ? k.w : k.z), max(l.x == ky ? l.y : l.x, l.z == ky ? l.w : l.z)));
            const uint32_t tok = ~ky & 2047;
            if (b < NFFN) bulk_e(sb + O_XSEL + (fw & 1) * 2064, prm.u + tok * 128, sb + B_XS, 2048);
            sched_fence(Z);
            if (fw == 3) mbar_arrive_e(sb + B_GO + 8);
            uint2 rc;
#pragma unroll 1
            do rc = ldr64(prm.S->stats + (b & 3) * 2048 + tok); while (__any_sync(~0u, (int)(rc.x ^ tag << 16) < 0) && ++it < 100000);
            sts128(sb + O_SEL + (fw & 1) * 16, tok, pk_bf(0.f, sigm(bf_hi(ky ^ (~((int)ky >> 31) | 0x80000000u)))), rc.y << 16, __float_as_uint(2.f * fabsf(__uint_as_float(rc.x))));
            __syncwarp();
            mbar_arrive_e(sb + B_SEL + (fw & 1) * 8);
        }
        if (b < NFFN) {
            float h[4][4] = {};
            uint4 A[8], B[2];
            const bool c1 = c & 1, c2 = c & 2;
            const uint32_t s2 = O_RNG3 + ((fw ^ 2) - fw) * 8192, bf = sb + B_FULL + fw * 8;
#define SLOT(n) ((n) % 3 == 2 ? s2 : (n) % 3 * 32768)
            auto ldA = [&](int k, int n, int hf) { A[k] = ldsm4t(wa[k & 3] + SLOT(n) + hf * 4096 + (k >> 2) * 2048); };
            auto half = [&](const uint4& x, int n, int hf) {
                sched_fence(Z);
#pragma unroll
                for (int k = 0; k < 8; k++) {
                    mma_bf(h[k & 3], A[k], k < 4 ? x.x : x.z, k < 4 ? x.y : x.w);
                    if (n >= 0) ldA(k, n, hf);
                }
            };
            mbar_wait(bf);
#pragma unroll
            for (int k = 0; k < 8; k++) ldA(k, 0, 0);
            mbar_wait(sb + B_XS);
            TS(fw == 1 ? 50 : 63);
            B[0] = ldsm4(xs);
#pragma unroll
            for (int n = 0; n < 4; n++) {
                TS(64 + fw + 4 * n);
                B[1] = ldsm4(xs + 64);
                half(B[0], n, 1);
                xs += xd;
                if (n < 3) { mbar_wait(bf + 32 * n + 32); B[0] = ldsm4(xs); }
                half(B[1], n < 3 ? n + 1 : -1, 0);
                TS(96 + fw + 4 * n);
                if (n < 3) {
                    sched_fence(Z);
                    if (n >= PACE) spin(t0 + W0 + ((b * WD) >> 7) + (fw + 4 * n + 12 - LEAD) * WD);
                    tma3d_e(sb + O_RING + fw * 8192 + SLOT(n), n ? &md : m1, (n ? q : fw + 12) * 64, n ? rk * 8 + fw + 4 * n - 4 : q, bf + 32 * n + 96);
                }
            }
#pragma unroll
            for (int j = 0; j < 4; j += 2)
                sts128(sb + O_RING + fw * 8192 + j * 256 + lane * 16, __float_as_uint(c2 ? h[j + 1][0] : h[j][0]), __float_as_uint(c2 ? h[j + 1][1] : h[j][1]),
                       __float_as_uint(c2 ? h[j + 1][2] : h[j][2]), __float_as_uint(c2 ? h[j + 1][3] : h[j][3]));
            if (fw >= 2) {
                bar_arrive(2, 128);
            } else {
                const uint32_t pa = sb + O_RING + fw * 512 + (lane >> 1) * 32 + (lane & 1) * 8, ha = sb + O_HT + fw * 64 + c * 16 + g * 2;
                mbar_wait(sb + B_SEL);
                mbar_wait(sb + B_SEL + 8);
                mbar_wait(sb + B_XF);
                const uint2 n0 = lds64(sb + O_SEL + 8), n1 = lds64(sb + O_SEL + 24);
                bar_sync(2, 128);
                TS(fw == 0 ? 51 : 63);
                float t[3][4];
#pragma unroll
                for (int j = 0; j < 4; j++) {
                    const uint2 p = lds64(pa + j * 8192);
                    t[0][j] = __uint_as_float(p.x); t[1][j] = __uint_as_float(p.y); t[2][j] = __uint_as_float(lds32(pa + j * 8192 + 16));
                }
                const float cs = (t[2][0] + t[2][1]) + (t[2][2] + t[2][3]);
                uint32_t v = pk_bf(fmaf(-__uint_as_float(n0.x), cs, (t[0][0] + t[0][1]) + (t[0][2] + t[0][3])) * __uint_as_float(n0.y),
                                   fmaf(-__uint_as_float(n1.x), cs, (t[1][0] + t[1][1]) + (t[1][2] + t[1][3])) * __uint_as_float(n1.y));
                if (rk == 0) v = pk_bf(silu(bf_lo(v)), silu(bf_hi(v)));
                asm volatile("st.async.shared::cluster.mbarrier::complete_tx::bytes.b32 [%0],%1,[%2];" ::"r"(pb + O_HX + fw * 128 + lane * 4), "r"(v), "r"(pb + B_H) : "memory");
                mbar_wait(sb + B_H);
                v = bmul(v, lds32(sb + O_HX + fw * 128 + lane * 4));
                sts16(ha, v); sts16(ha + 144, v >> 16);
                __syncwarp();
                asm volatile("{.reg .pred p; elect.sync _|p,0xffffffff; @p mbarrier.arrive.shared.b64 _,[%0],4;}" ::"r"(sb + B_HR) : "memory");
            }
#pragma unroll
            for (int n = 4; n < 6; n++) {
                mbar_wait(bf + 32 * n);
                TS(64 + fw + 4 * n);
#pragma unroll
                for (int k = 0; k < 8; k++) ldA(k, n, 0);
                if (n == 4) {
                    mbar_wait(sb + B_HR);
                    TS(fw == 0 ? 52 : 63);
                    B[0] = ldsm4(hs); B[1] = ldsm4(hs + 64);
                }
#pragma unroll
                for (int k = 0; k < 16; k++) h[k >> 2][k & 3] = 0.f;
                half(B[0], n, 1);
                half(B[1], -1, 0);
#define PICK(k) __float_as_uint(c2 ? (c1 ? h[3][k] : h[2][k]) : (c1 ? h[1][k] : h[0][k]))
                uint2* yo = prm.S->yp + dst + (n - 4) * 16 * 112 * 8;
                str64(yo, (PICK(0) & ~1u) | (ep & 1), PICK(1)); str64(yo + 448, (PICK(2) & ~1u) | (ep & 1), PICK(3));
                TS(96 + fw + 4 * n);
            }
            TS(fw == 0 ? 63 : 52 + fw);
        }
        if (!NOFIX && fw == 0) {
            mbar_wait(sb + B_SEL);
            mbar_wait(sb + B_SEL + 8);
            const uint4 sel = lds128(sb + O_SEL + (lane & 8) * 2);
            const uint32_t ch = 2 * c + (g & 1), go = sel.x * 1024 + b * 8 + ch;
            uint32_t xv;
            uint32_t sa = sb + O_RAW - TS8 + (sel.x >> 4) * BS + ch * 32 + (sel.x & 15) * 2;
            uint32_t ba = __reduce_max_sync(~0u, sel.x >> 8);
            ba = sb + B_Y + (ba == 7 ? 4 : ba >> 1) * 8;
            asm volatile("ld.global.nc.u16 %0,[%1];" : "=r"(xv) : "l"((const uint16_t*)prm.u + go) : "memory");
            xv <<= 16;
            uint32_t j0 = 0, xn = __float_as_uint(bfr(bfr(__uint_as_float(xv) - __uint_as_float(sel.z)) * __uint_as_float(sel.w)));
            pin4(xv, xn, sa, j0, Z);
            const uint4* yp = (const uint4*)prm.S->yp + b * 224 + lane;
            spin(t0 + TFIX);
            uint4 v[7];
            int it = 0;
            uint32_t bad, sv;
#pragma unroll 1
            do {
#pragma unroll
                for (int j = 0; j < 7; j++) v[j] = ldr128(yp + j * 32);
                mbar_wait(ba);
                sv = bmul(lds16(sa), lds16(sb + O_SEL + 48 + ch * 2));
                bad = 0;
#pragma unroll
                for (int j = 0; j < 7; j++) asm volatile("{.reg .b32 t; lop3.b32 t,%1,%2,%3,0x7e; or.b32 %0,%0,t;}" : "+r"(bad) : "r"(v[j].x), "r"(ep), "r"(v[j].z));
            } while (__any_sync(~0u, bad & 1) && ++it < 100000);
            TV(57, it);
            float y[4];
#pragma unroll
            for (int k = 0; k < 4; k++)
                y[k] = ((__uint_as_float(comp(v[0], k)) + __uint_as_float(comp(v[1], k))) + (__uint_as_float(comp(v[2], k)) + __uint_as_float(comp(v[3], k)))) +
                       ((__uint_as_float(comp(v[4], k)) + __uint_as_float(comp(v[5], k))) + __uint_as_float(comp(v[6], k)));
            const bool b2 = lane & 4, b3 = lane & 8;
            const float y0 = (b2 ? y[2] : y[0]) + __shfl_xor_sync(~0u, b2 ? y[0] : y[2], 4), y1 = (b2 ? y[3] : y[1]) + __shfl_xor_sync(~0u, b2 ? y[1] : y[3], 4);
            float t = (b3 ? y1 : y0) + __shfl_xor_sync(~0u, b3 ? y0 : y1, 8);
            t += __shfl_xor_sync(~0u, t, 16);
            const float gt = bfr(silu(bfr(__uint_as_float(xn) + bfr(bfr(t) * __uint_as_float(sel.y)))));
            TS(56);
            ((uint16_t*)prm.out)[go] = pk_bf(fmaf(bf_lo(sv), gt, __uint_as_float(xv)), 0.f);
            TS(7);
        }
        TDUMP;
    }
}

typedef CUresult (*EncFn)(CUtensorMap*, CUtensorMapDataType, cuuint32_t, void*, const cuuint64_t*, const cuuint64_t*,
                          const cuuint32_t*, const cuuint32_t*, CUtensorMapInterleave, CUtensorMapSwizzle,
                          CUtensorMapL2promotion, CUtensorMapFloatOOBfill);

void make_map(EncFn f, CUtensorMap* m, const void* p, int rank, const cuuint64_t* gd, const cuuint64_t* gs,
              const cuuint32_t* bd, CUtensorMapSwizzle sw) {
    const cuuint32_t es[5] = {1, 1, 1, 1, 1};
    f(m, CU_TENSOR_MAP_DATA_TYPE_BFLOAT16, rank, const_cast<void*>(p), gd, gs, bd, es, CU_TENSOR_MAP_INTERLEAVE_NONE, sw,
      CU_TENSOR_MAP_L2_PROMOTION_NONE, CU_TENSOR_MAP_FLOAT_OOB_FILL_NONE);
}

}

extern "C" void kernel_launch(void* const* d_in, const int* in_sizes, int n_in, void* d_out, int out_size) {
    (void)in_sizes; (void)n_in; (void)out_size;
    void* fp = nullptr;
    cudaDriverEntryPointQueryResult qr;
    cudaGetDriverEntryPoint("cuTensorMapEncodeTiled", &fp, cudaEnableDefault, &qr);
    EncFn enc = (EncFn)fp;
    Maps maps;
    CUtensorMap &mg = maps.m[0], &mu = maps.m[1], &md = maps.m[2], &mx = maps.m[3], &mo = maps.m[4];
    {
        const cuuint64_t gd[3] = {64, 1024, 56}, gs[2] = {7168, 128};
        const cuuint32_t bd[3] = {64, 64, 1};
        make_map(enc, &mg, d_in[9], 3, gd, gs, bd, CU_TENSOR_MAP_SWIZZLE_128B);
        make_map(enc, &mu, d_in[10], 3, gd, gs, bd, CU_TENSOR_MAP_SWIZZLE_128B);
    }
    {
        const cuuint64_t gd[3] = {64, 3584, 16}, gs[2] = {2048, 128};
        const cuuint32_t bd[3] = {64, 64, 1};
        make_map(enc, &md, d_in[11], 3, gd, gs, bd, CU_TENSOR_MAP_SWIZZLE_128B);
    }
    {
        const cuuint64_t gd[5] = {1024, 2, 32, 8, 4}, gs[4] = {16384, 131072, 2048, 32768};
        const cuuint32_t bd[5] = {16, 2, 2, 8, 4}, bo[5] = {16, 2, 2, 8, 1};
        make_map(enc, &mx, d_in[0], 5, gd, gs, bd, CU_TENSOR_MAP_SWIZZLE_32B);
        make_map(enc, &mo, d_out, 5, gd, gs, bo, CU_TENSOR_MAP_SWIZZLE_32B);
    }
    Params p;
    p.u = (const uint4*)d_in[0]; p.logA = (const uint2*)d_in[1]; p.Aim = (const uint2*)d_in[2];
    p.Cre = (const uint2*)d_in[3]; p.Cim = (const uint2*)d_in[4];
    p.logdt = (const uint16_t*)d_in[5]; p.Dsk = (const uint16_t*)d_in[6]; p.wr = (const uint4*)d_in[8];
    p.out = (uint4*)d_out;
    void* sp = nullptr;
    cudaGetSymbolAddress(&sp, g_scratch);
    p.S = (Scratch*)sp; p.zero = 0;
    cudaFuncSetAttribute(fused_kernel, cudaFuncAttributeMaxDynamicSharedMemorySize, SMEM_BYTES + 512);
    fused_kernel<<<128, 640, SMEM_BYTES + 512, cudaStreamPerThread>>>(p, maps);
}
```
